```python
import torch

def _softmax(x, axis=-1):
    return torch.softmax(x, dim=axis)
def _gelu(x):
    return torch.nn.functional.gelu(x, approximate="tanh")
def _silu(x):
    return torch.nn.functional.silu(x)
def _sigmoid(x):
    return torch.sigmoid(x)
def _layernorm(x, axis=-1, eps=1e-5):
    m = x.mean(dim=axis, keepdim=True)
    v = x.var(dim=axis, keepdim=True, unbiased=False)
    return (x - m) / torch.sqrt(v + eps)
def _scatter_add(tgt, idx, src, axis=0):
    return tgt.clone().index_add_(axis, idx, src)
def _segment_sum(src, seg, n):
    out = torch.zeros((n,) + src.shape[1:], dtype=src.dtype)
    return out.index_add_(0, seg, src)
def _pad(x, pw):
    flat = tuple(v for pair in reversed(pw) for v in pair)
    return torch.nn.functional.pad(x, flat)

kernel_name = 'recurrent_scan__ssm_conv_s4__dense_activation_silu__prompt'

def setup_inputs():

    _w = (lambda a: (lambda t: t.to(torch.bfloat16) if t.is_floating_point() else t)(torch.as_tensor(a)))
    def _A_setup():
        B, L, D, N = 1, 2048, 640, 192
        A_re = -(lambda _x: torch.exp(torch.as_tensor(_x)))((lambda *s: torch.randn(*s, dtype=torch.bfloat16) * 3.2)(D, N))
        A_im = torch.pi * (lambda *s: torch.randn(*s, dtype=torch.bfloat16) * 0.2)(D, N)
        B_re = (lambda *s: torch.randn(*s, dtype=torch.bfloat16) * 0.2)(D, N)
        B_im = (lambda *s: torch.randn(*s, dtype=torch.bfloat16) * 0.2)(D, N)
        C_re = (lambda *s: torch.randn(*s, dtype=torch.bfloat16) * 0.2)(D, N)
        C_im = (lambda *s: torch.randn(*s, dtype=torch.bfloat16) * 0.2)(D, N)
        log_dt = (lambda *s: torch.randn(*s, dtype=torch.bfloat16) * 0.2)(D) * 0.5 - 4.0
        Dskip = (lambda *s: torch.randn(*s, dtype=torch.bfloat16) * 0.2)(D)
        return {
            "u": _w((lambda *s: torch.randn(*s, dtype=torch.bfloat16) * 0.05)(B, L, D)),
            "A_re": _w(A_re),
            "A_im": _w(A_im),
            "B_re": _w(B_re),
            "B_im": _w(B_im),
            "C_re": _w(C_re),
            "C_im": _w(C_im),
            "log_dt": _w(log_dt),
            "Dskip": _w(Dskip),
        }
    _A_in = _A_setup()

    def _B_setup():
        B, S, D, F = 1, 2048, 640, 1536
        return {
            "x": _w((lambda *s: torch.randn(*s, dtype=torch.bfloat16) * 0.05)(B, S, D)),
            "w1": _w((lambda *s: torch.randn(*s, dtype=torch.bfloat16) * 0.8)(D, F) * (D ** -0.5)),
            "w2": _w((lambda *s: torch.randn(*s, dtype=torch.bfloat16) * 0.1)(F, D) * (F ** -0.5)),
        }
    _B_in = _B_setup()

    return {
        "A_u": _A_in["u"],
        "A_A_re": _A_in["A_re"],
        "A_A_im": _A_in["A_im"],
        "A_B_re": _A_in["B_re"],
        "A_B_im": _A_in["B_im"],
        "A_C_re": _A_in["C_re"],
        "A_C_im": _A_in["C_im"],
        "A_log_dt": _A_in["log_dt"],
        "A_Dskip": _A_in["Dskip"],
        "B_x": _B_in["x"],
        "B_w1": _B_in["w1"],
        "B_w2": _B_in["w2"],
    }

def reference(A_u, A_A_re, A_A_im, A_B_re, A_B_im, A_C_re, A_C_im, A_log_dt, A_Dskip, B_x, B_w1, B_w2):
    def _A_ref(u, A_re, A_im, B_re, B_im, C_re, C_im, log_dt, Dskip):
        Bsz, L, D = u.shape
        dt = torch.exp(log_dt)[:, None]
        A = A_re + 1j * A_im
        Bc = B_re + 1j * B_im
        Cc = C_re + 1j * C_im
        logdA = dt * A
        dB = dt * Bc
        l = (lambda x, dt: x.to(dt))(torch.arange(L), A_re.dtype)
        P = torch.exp(logdA[:, :, None] * l[None, None, :])
        K = torch.einsum("dn,dnl,dn->dl", Cc, P, dB).real
        L2 = 2 * L
        Kp = _pad(K, ((0, 0), (0, L)))
        up = (lambda x, *d: x.permute(*d))(u, 0, 2, 1)
        up = _pad(up, ((0, 0), (0, 0), (0, L)))
        Kf = (lambda x, axes=(-2,-1): torch.fft.rfft2(x.float(), dim=axes))(Kp[:, None, :], axes=(-2, -1))
        Uf = (lambda x, axes=(-2,-1): torch.fft.rfft2(x.float(), dim=axes))(up[:, :, None, :], axes=(-2, -1))
        Yf = Uf * Kf[None, :, :, :]
        y = (lambda x, s, axes=(-2,-1): torch.fft.irfft2(x, s=s, dim=axes).to(torch.bfloat16))(Yf, (1, L2), axes=(-2, -1))[:, :, 0, :L]
        y = (lambda x, *d: x.permute(*d))(y, 0, 2, 1) + u * Dskip[None, None, :]
        return y

    def _B_ref(x, w1, w2):
        h = torch.einsum("bsd,df->bsf", x, w1)
        h = _silu(h)
        out = torch.einsum("bsf,fd->bsd", h, w2)
        return out

    x = A_u
    xn = _layernorm(x, axis=-1)
    s = _A_ref(xn, A_A_re, A_A_im, A_B_re, A_B_im, A_C_re, A_C_im, A_log_dt, A_Dskip)
    g = _silu(_B_ref(xn, B_w1, B_w2))
    return x + s * g
```

```cpp
#include <cuda_runtime.h>
#include <cuda_bf16.h>
#include <cuda_fp16.h>
#include <cuda.h>
#include <stdint.h>

namespace {

constexpr int L_ = 2048, D_ = 640, NM_ = 192, F_ = 1536;
constexpr int NTHREADS = 512;

constexpr uint32_t G1_STAGE = 40960;
constexpr uint32_t Y_ = 3 * G1_STAGE;
constexpr uint32_t WCH = 13184;
constexpr uint32_t W5_OFF = 0, W5_PS = 1728;
constexpr uint32_t W3_OFF = 3456, W3_PS = 1600;
constexpr uint32_t W9_OFF = 6656, W7_OFF = 8832, WM_OFF = 11008, W9_PS = 1088;
constexpr uint32_t SM_W = Y_;
constexpr uint32_t KBUF = 2880;
constexpr uint32_t SM_W2ST = Y_ + 43264;
constexpr uint32_t SM_KH = SM_W2ST + 15360;
constexpr uint32_t KH_CH = 1296;
constexpr uint32_t SM_U = Y_ + 65920;
constexpr uint32_t LN_PITCH = 1296;
constexpr uint32_t SM_T = SM_U + 21760;
constexpr uint32_t TCH = 3584;
constexpr uint32_t SM_CS = SM_T + 5 * TCH;
constexpr uint32_t SM_ST = SM_CS + 768;
constexpr uint32_t SM_BAR = SM_ST + 1024;
constexpr uint32_t SM_END = SM_BAR + 512;
constexpr uint32_t SMEM_BYTES = SM_END + 1024;
static_assert(SMEM_BYTES <= 232448, "smem");
static_assert(SM_KH + 5 * KH_CH <= SM_U, "smem alias");
static_assert((SM_W2ST % 256) == 0, "align");
constexpr uint32_t B_FULL1 = SM_BAR, B_EMPTY1 = SM_BAR + 24, B_FULL2 = SM_BAR + 48, B_EMPTY2 = SM_BAR + 112;
constexpr uint32_t B_W2LD = SM_BAR + 176, B_ULD = SM_BAR + 184, B_HST = SM_BAR + 192, B_ST1RD = SM_BAR + 216;
constexpr uint32_t B_G1DONE = SM_BAR + 224, B_CVDONE = SM_BAR + 232, B_XS = SM_BAR + 240, SM_EPOCH = SM_BAR + 256;
__host__ __device__ constexpr uint32_t g2a(int s) { return s < 5 ? s * 16384u : Y_ + (s - 5) * 16384u; }
__host__ __device__ constexpr uint32_t g2b(int s) { return s < 4 ? 81920u + s * 10240u : Y_ + 49152u + (s - 4) * 10240u; }
constexpr uint32_t SM_HST = 2 * 16384;
constexpr uint32_t SM_XT = 0;
constexpr uint32_t SM_S = 81920;

__device__ __align__(1024) uint8_t g_uT[128 * D_ * 32];
__device__ __align__(1024) uint8_t g_h[16 * 24 * 16384];
__device__ __align__(1024) uint8_t g_w2r[8 * 24 * 10240];
__device__ __align__(1024) uint32_t g_s[16 * D_ * 64];
__device__ __align__(1024) float g_csp[16 * F_];
__device__ __align__(1024) float2 g_stats[L_];
__device__ __align__(1024) unsigned g_cnt[64 * 32];
constexpr int C_CHK = 0, C_F2 = 1, C_F4 = 2, C_F3 = 10;
#define TS(i)
#define TS1(i)

struct Params {
  const __nv_bfloat16 *x, *are, *aim, *bre, *bim, *cre, *cim, *logdt, *dskip, *w1;
  int use_smid;
};

__device__ __forceinline__ bool elect_one() {
  uint32_t p;
  asm volatile("{.reg .pred P; elect.sync _|P, 0xffffffff; selp.u32 %0,1,0,P;}" : "=r"(p));
  return p;
}
__device__ __forceinline__ void mbar_init(uint32_t a, uint32_t c) {
  asm volatile("mbarrier.init.shared::cta.b64 [%0], %1;" ::"r"(a), "r"(c) : "memory");
}
__device__ __forceinline__ void mbar_expect(uint32_t a, uint32_t b) {
  asm volatile("mbarrier.arrive.expect_tx.shared::cta.b64 _, [%0], %1;" ::"r"(a), "r"(b) : "memory");
}
__device__ __forceinline__ void mbar_arrive(uint32_t a) {
  asm volatile("mbarrier.arrive.shared::cta.b64 _, [%0];" ::"r"(a) : "memory");
}
__device__ __forceinline__ void mbar_wait(uint32_t a, uint32_t ph) {
  asm volatile(
      "{.reg .pred p; .reg .u32 n; mov.u32 n, 0;\n"
      "LW%=: mbarrier.try_wait.parity.shared::cta.b64 p, [%0], %1;\n"
      "@p bra LD%=; add.u32 n, n, 1; setp.lt.u32 p, n, 200000; @p bra LW%=;\n"
      "LD%=: }" ::"r"(a), "r"(ph) : "memory");
}
__device__ __forceinline__ void bar_sync(int id, int n) { asm volatile("bar.sync %0, %1;" ::"r"(id), "r"(n) : "memory"); }
__device__ __forceinline__ void fence_async() { asm volatile("fence.proxy.async;" ::: "memory"); }
__device__ __forceinline__ void fence_async_smem() { asm volatile("fence.proxy.async.shared::cta;" ::: "memory"); }
__device__ __forceinline__ void red_release(unsigned* p) {
  asm volatile("red.release.gpu.global.add.u32 [%0], 1;" ::"l"(p) : "memory");
}
__device__ __forceinline__ void poll_flag(const unsigned* p, unsigned target) {
  for (int n = 0; n < 100000; n++) {
    unsigned v;
    asm volatile("ld.acquire.gpu.global.u32 %0, [%1];" : "=r"(v) : "l"(p) : "memory");
    if ((int)(v - target) >= 0) break;
  }
}
__device__ __forceinline__ void bulk_g2s(uint32_t dst, const void* src, uint32_t bytes, uint32_t bar) {
  asm volatile("cp.async.bulk.shared::cluster.global.mbarrier::complete_tx::bytes [%0], [%1], %2, [%3];" ::"r"(dst),
               "l"(src), "r"(bytes), "r"(bar) : "memory");
}
__device__ __forceinline__ void bulk_s2g(void* dst, uint32_t src, uint32_t bytes) {
  asm volatile("cp.async.bulk.global.shared::cta.bulk_group [%0], [%1], %2;" ::"l"(dst), "r"(src), "r"(bytes) : "memory");
}
__device__ __forceinline__ void bulk_prefetch(const void* src, uint32_t bytes) {
  asm volatile("cp.async.bulk.prefetch.L2.global [%0], %1;" ::"l"(src), "r"(bytes) : "memory");
}
__device__ __forceinline__ void bulk_commit() { asm volatile("cp.async.bulk.commit_group;" ::: "memory"); }
__device__ __forceinline__ void bulk_wait0() { asm volatile("cp.async.bulk.wait_group 0;" ::: "memory"); }
__device__ __forceinline__ void bulk_wait0_read() { asm volatile("cp.async.bulk.wait_group.read 0;" ::: "memory"); }
__device__ __forceinline__ void tma2d(uint32_t dst, const CUtensorMap* m, int c0, int c1, uint32_t bar) {
  asm volatile("cp.async.bulk.tensor.2d.shared::cluster.global.mbarrier::complete_tx::bytes [%0], [%1, {%3, %4}], [%2];"
               ::"r"(dst), "l"(m), "r"(bar), "r"(c0), "r"(c1) : "memory");
}
__device__ __forceinline__ void tma3d(uint32_t dst, const CUtensorMap* m, int c0, int c1, int c2, uint32_t bar) {
  asm volatile("cp.async.bulk.tensor.3d.shared::cluster.global.mbarrier::complete_tx::bytes [%0], [%1, {%3, %4, %5}], [%2];"
               ::"r"(dst), "l"(m), "r"(bar), "r"(c0), "r"(c1), "r"(c2) : "memory");
}
__device__ __forceinline__ void tma2d_store(const CUtensorMap* m, uint32_t src, int c0, int c1) {
  asm volatile("cp.async.bulk.tensor.2d.global.shared::cta.bulk_group [%0, {%2, %3}], [%1];" ::"l"(m), "r"(src), "r"(c0),
               "r"(c1) : "memory");
}
__device__ __forceinline__ void tm_prefetch(const CUtensorMap* m) {
  asm volatile("prefetch.tensormap [%0];" ::"l"(m) : "memory");
}
__device__ __forceinline__ uint64_t mkdesc(uint32_t addr, uint32_t lbo, uint32_t sbo, uint32_t mode) {
  return (uint64_t)((addr & 0x3FFFF) >> 4) | ((uint64_t)(lbo >> 4) << 16) | ((uint64_t)(sbo >> 4) << 32) |
         ((uint64_t)mode << 62);
}
__device__ __forceinline__ void wg_fence() { asm volatile("wgmma.fence.sync.aligned;" ::: "memory"); }
__device__ __forceinline__ void wg_commit() { asm volatile("wgmma.commit_group.sync.aligned;" ::: "memory"); }
template <int N> __device__ __forceinline__ void wg_wait() {
  asm volatile("wgmma.wait_group.sync.aligned %0;" ::"n"(N) : "memory");
}
__device__ __forceinline__ void wgmma_n192(float (&d)[96], uint64_t da, uint64_t db, int acc) {
  asm volatile(
      "{.reg .pred p; setp.ne.b32 p, %98, 0;\n"
      "wgmma.mma_async.sync.aligned.m64n192k16.f32.bf16.bf16 {"
      "%0,%1,%2,%3,%4,%5,%6,%7,%8,%9,%10,%11,%12,%13,%14,%15,"
      "%16,%17,%18,%19,%20,%21,%22,%23,%24,%25,%26,%27,%28,%29,%30,%31,"
      "%32,%33,%34,%35,%36,%37,%38,%39,%40,%41,%42,%43,%44,%45,%46,%47,"
      "%48,%49,%50,%51,%52,%53,%54,%55,%56,%57,%58,%59,%60,%61,%62,%63,"
      "%64,%65,%66,%67,%68,%69,%70,%71,%72,%73,%74,%75,%76,%77,%78,%79,"
      "%80,%81,%82,%83,%84,%85,%86,%87,%88,%89,%90,%91,%92,%93,%94,%95"
      "}, %96, %97, p, 1, 1, 0, 1;}\n"
      :
        "+f"(d[0]), "+f"(d[1]), "+f"(d[2]), "+f"(d[3]), "+f"(d[4]), "+f"(d[5]), "+f"(d[6]), "+f"(d[7]),
        "+f"(d[8]), "+f"(d[9]), "+f"(d[10]), "+f"(d[11]), "+f"(d[12]), "+f"(d[13]), "+f"(d[14]), "+f"(d[15]),
        "+f"(d[16]), "+f"(d[17]), "+f"(d[18]), "+f"(d[19]), "+f"(d[20]), "+f"(d[21]), "+f"(d[22]), "+f"(d[23]),
        "+f"(d[24]), "+f"(d[25]), "+f"(d[26]), "+f"(d[27]), "+f"(d[28]), "+f"(d[29]), "+f"(d[30]), "+f"(d[31]),
        "+f"(d[32]), "+f"(d[33]), "+f"(d[34]), "+f"(d[35]), "+f"(d[36]), "+f"(d[37]), "+f"(d[38]), "+f"(d[39]),
        "+f"(d[40]), "+f"(d[41]), "+f"(d[42]), "+f"(d[43]), "+f"(d[44]), "+f"(d[45]), "+f"(d[46]), "+f"(d[47]),
        "+f"(d[48]), "+f"(d[49]), "+f"(d[50]), "+f"(d[51]), "+f"(d[52]), "+f"(d[53]), "+f"(d[54]), "+f"(d[55]),
        "+f"(d[56]), "+f"(d[57]), "+f"(d[58]), "+f"(d[59]), "+f"(d[60]), "+f"(d[61]), "+f"(d[62]), "+f"(d[63]),
        "+f"(d[64]), "+f"(d[65]), "+f"(d[66]), "+f"(d[67]), "+f"(d[68]), "+f"(d[69]), "+f"(d[70]), "+f"(d[71]),
        "+f"(d[72]), "+f"(d[73]), "+f"(d[74]), "+f"(d[75]), "+f"(d[76]), "+f"(d[77]), "+f"(d[78]), "+f"(d[79]),
        "+f"(d[80]), "+f"(d[81]), "+f"(d[82]), "+f"(d[83]), "+f"(d[84]), "+f"(d[85]), "+f"(d[86]), "+f"(d[87]),
        "+f"(d[88]), "+f"(d[89]), "+f"(d[90]), "+f"(d[91]), "+f"(d[92]), "+f"(d[93]), "+f"(d[94]), "+f"(d[95])
      : "l"(da), "l"(db), "r"(acc));
}

__device__ __forceinline__ void wgmma_n80(float (&d)[40], uint64_t da, uint64_t db, int acc) {
  asm volatile(
      "{.reg .pred p; setp.ne.b32 p, %42, 0;\n"
      "wgmma.mma_async.sync.aligned.m64n80k16.f32.bf16.bf16 {"
      "%0,%1,%2,%3,%4,%5,%6,%7,%8,%9,%10,%11,%12,%13,%14,%15,"
      "%16,%17,%18,%19,%20,%21,%22,%23,%24,%25,%26,%27,%28,%29,%30,%31,"
      "%32,%33,%34,%35,%36,%37,%38,%39"
      "}, %40, %41, p, 1, 1, 0, 1;}\n"
      :
        "+f"(d[0]), "+f"(d[1]), "+f"(d[2]), "+f"(d[3]), "+f"(d[4]), "+f"(d[5]), "+f"(d[6]), "+f"(d[7]),
        "+f"(d[8]), "+f"(d[9]), "+f"(d[10]), "+f"(d[11]), "+f"(d[12]), "+f"(d[13]), "+f"(d[14]), "+f"(d[15]),
        "+f"(d[16]), "+f"(d[17]), "+f"(d[18]), "+f"(d[19]), "+f"(d[20]), "+f"(d[21]), "+f"(d[22]), "+f"(d[23]),
        "+f"(d[24]), "+f"(d[25]), "+f"(d[26]), "+f"(d[27]), "+f"(d[28]), "+f"(d[29]), "+f"(d[30]), "+f"(d[31]),
        "+f"(d[32]), "+f"(d[33]), "+f"(d[34]), "+f"(d[35]), "+f"(d[36]), "+f"(d[37]), "+f"(d[38]), "+f"(d[39])
      : "l"(da), "l"(db), "r"(acc));
}

__device__ __forceinline__ void mma16816(float (&d)[4], uint32_t a0, uint32_t a1, uint32_t a2, uint32_t a3, uint32_t b0,
                                         uint32_t b1) {
  asm("mma.sync.aligned.m16n8k16.row.col.f32.f16.f16.f32 {%0,%1,%2,%3},{%4,%5,%6,%7},{%8,%9},{%0,%1,%2,%3};"
      : "+f"(d[0]), "+f"(d[1]), "+f"(d[2]), "+f"(d[3]) : "r"(a0), "r"(a1), "r"(a2), "r"(a3), "r"(b0), "r"(b1));
}
__device__ __forceinline__ void mma1688(float (&d)[4], uint32_t a0, uint32_t a1, uint32_t b0) {
  asm("mma.sync.aligned.m16n8k8.row.col.f32.f16.f16.f32 {%0,%1,%2,%3},{%4,%5},{%6},{%0,%1,%2,%3};"
      : "+f"(d[0]), "+f"(d[1]), "+f"(d[2]), "+f"(d[3]) : "r"(a0), "r"(a1), "r"(b0));
}
__device__ __forceinline__ void ldsm4(uint32_t a, uint32_t& r0, uint32_t& r1, uint32_t& r2, uint32_t& r3) {
  asm volatile("ldmatrix.sync.aligned.m8n8.x4.shared.b16 {%0,%1,%2,%3}, [%4];"
               : "=r"(r0), "=r"(r1), "=r"(r2), "=r"(r3) : "r"(a) : "memory");
}
__device__ __forceinline__ void ldsm2(uint32_t a, uint32_t& r0, uint32_t& r1) {
  asm volatile("ldmatrix.sync.aligned.m8n8.x2.shared.b16 {%0,%1}, [%2];" : "=r"(r0), "=r"(r1) : "r"(a) : "memory");
}
__device__ __forceinline__ void ldsm4t(uint32_t a, uint32_t& r0, uint32_t& r1, uint32_t& r2, uint32_t& r3) {
  asm volatile("ldmatrix.sync.aligned.m8n8.x4.trans.shared.b16 {%0,%1,%2,%3}, [%4];"
               : "=r"(r0), "=r"(r1), "=r"(r2), "=r"(r3) : "r"(a) : "memory");
}
__device__ __forceinline__ void ldsm2t(uint32_t a, uint32_t& r0, uint32_t& r1) {
  asm volatile("ldmatrix.sync.aligned.m8n8.x2.trans.shared.b16 {%0,%1}, [%2];" : "=r"(r0), "=r"(r1) : "r"(a) : "memory");
}
__device__ __forceinline__ void ldsm1t(uint32_t a, uint32_t& r0) {
  asm volatile("ldmatrix.sync.aligned.m8n8.x1.trans.shared.b16 {%0}, [%1];" : "=r"(r0) : "r"(a) : "memory");
}
__device__ __forceinline__ void stsm4(uint32_t a, uint32_t r0, uint32_t r1, uint32_t r2, uint32_t r3) {
  asm volatile("stmatrix.sync.aligned.m8n8.x4.shared.b16 [%0], {%1,%2,%3,%4};" ::"r"(a), "r"(r0), "r"(r1), "r"(r2), "r"(r3)
               : "memory");
}
__device__ __forceinline__ uint32_t lds32(uint32_t a) {
  uint32_t v; asm volatile("ld.shared.u32 %0, [%1];" : "=r"(v) : "r"(a) : "memory"); return v;
}
__device__ __forceinline__ uint32_t lds16(uint32_t a) {
  uint16_t v; asm volatile("ld.shared.u16 %0, [%1];" : "=h"(v) : "r"(a) : "memory"); return v;
}
__device__ __forceinline__ float ldsf(uint32_t a) { return __uint_as_float(lds32(a)); }
__device__ __forceinline__ float2 lds64f(uint32_t a) {
  float2 v; asm volatile("ld.shared.v2.f32 {%0,%1}, [%2];" : "=f"(v.x), "=f"(v.y) : "r"(a) : "memory"); return v;
}
__device__ __forceinline__ uint4 lds128(uint32_t a) {
  uint4 v;
  asm volatile("ld.shared.v4.u32 {%0,%1,%2,%3}, [%4];" : "=r"(v.x), "=r"(v.y), "=r"(v.z), "=r"(v.w) : "r"(a) : "memory");
  return v;
}
__device__ __forceinline__ void sts16(uint32_t a, uint32_t v) {
  asm volatile("st.shared.u16 [%0], %1;" ::"r"(a), "h"((uint16_t)v) : "memory");
}
__device__ __forceinline__ void sts32(uint32_t a, uint32_t v) { asm volatile("st.shared.u32 [%0], %1;" ::"r"(a), "r"(v) : "memory"); }
__device__ __forceinline__ void sts64(uint32_t a, uint32_t x, uint32_t y) {
  asm volatile("st.shared.v2.u32 [%0], {%1,%2};" ::"r"(a), "r"(x), "r"(y) : "memory");
}
__device__ __forceinline__ void sts64f(uint32_t a, float x, float y) { sts64(a, __float_as_uint(x), __float_as_uint(y)); }
__device__ __forceinline__ void sts128(uint32_t a, uint32_t x, uint32_t y, uint32_t z, uint32_t w) {
  asm volatile("st.shared.v4.u32 [%0], {%1,%2,%3,%4};" ::"r"(a), "r"(x), "r"(y), "r"(z), "r"(w) : "memory");
}
__device__ __forceinline__ uint32_t pack_h2(float lo, float hi) {
  uint32_t r; asm("cvt.rn.f16x2.f32 %0, %1, %2;" : "=r"(r) : "f"(hi), "f"(lo)); return r;
}
__device__ __forceinline__ uint32_t pack_b2(float lo, float hi) {
  uint32_t r; asm("cvt.rn.bf16x2.f32 %0, %1, %2;" : "=r"(r) : "f"(hi), "f"(lo)); return r;
}
__device__ __forceinline__ uint32_t hadd2(uint32_t a, uint32_t b) {
  uint32_t r; asm("add.rn.f16x2 %0, %1, %2;" : "=r"(r) : "r"(a), "r"(b)); return r;
}
__device__ __forceinline__ uint32_t hmul2(uint32_t a, uint32_t b) {
  uint32_t r; asm("mul.rn.f16x2 %0, %1, %2;" : "=r"(r) : "r"(a), "r"(b)); return r;
}
__device__ __forceinline__ uint32_t hfma2(uint32_t a, uint32_t b, uint32_t c) {
  uint32_t r; asm("fma.rn.f16x2 %0, %1, %2, %3;" : "=r"(r) : "r"(a), "r"(b), "r"(c)); return r;
}
__device__ __forceinline__ uint32_t hfnma2(uint32_t a, uint32_t b, uint32_t c) {
  uint32_t r;
  asm("{.reg .b32 t; neg.f16x2 t, %1; fma.rn.f16x2 %0, t, %2, %3;}" : "=r"(r) : "r"(a), "r"(b), "r"(c));
  return r;
}
__device__ __forceinline__ uint32_t badd2(uint32_t a, uint32_t b) {
  uint32_t r; asm("add.rn.bf16x2 %0, %1, %2;" : "=r"(r) : "r"(a), "r"(b)); return r;
}
__device__ __forceinline__ float bf_lo(uint32_t v) { return __uint_as_float(v << 16); }
__device__ __forceinline__ float bf_hi(uint32_t v) { return __uint_as_float(v & 0xffff0000u); }
__device__ __forceinline__ float bf_round(float v) { return __bfloat162float(__float2bfloat16_rn(v)); }
__device__ __forceinline__ float tanh_fast(float v) { float r; asm("tanh.approx.f32 %0, %1;" : "=f"(r) : "f"(v)); return r; }
__device__ __forceinline__ float ex2_fast(float v) { float r; asm("ex2.approx.ftz.f32 %0, %1;" : "=f"(r) : "f"(v)); return r; }
__device__ __forceinline__ uint32_t ldg32(const void* p) {
  uint32_t v; asm volatile("ld.global.nc.u32 %0, [%1];" : "=r"(v) : "l"(p)); return v;
}

struct c2 { float r, i; };
__device__ __forceinline__ c2 cmul(c2 a, c2 b) {
  c2 o; o.r = fmaf(a.r, b.r, -a.i * b.i); o.i = fmaf(a.r, b.i, a.i * b.r); return o;
}
__device__ __forceinline__ c2 zpow(float a2, float tau, float e) {
  float mag = ex2_fast(a2 * e);
  float t = tau * e;
  float k = __fadd_rn(__fadd_rn(t, 12582912.f), -12582912.f);
  float ang = __fsub_rn(t, k) * 6.283185307179586f;
  c2 o; o.r = mag * __cosf(ang); o.i = mag * __sinf(ang); return o;
}

__device__ __forceinline__ void kgen_warp(uint32_t kb, int lane, uint32_t p_are, uint32_t p_aim, uint32_t p_bre,
                                          uint32_t p_bim, uint32_t p_cre, uint32_t p_cim, float dt) {
  const int g = lane >> 2, c = lane & 3;
  float a2[2], tau[2];
  c2 W[2];
  {
    const float k1 = 1.4426950408889634f, k2 = 0.15915494309189535f;
    a2[0] = (dt * bf_lo(p_are)) * k1; a2[1] = (dt * bf_hi(p_are)) * k1;
    tau[0] = (dt * bf_lo(p_aim)) * k2; tau[1] = (dt * bf_hi(p_aim)) * k2;
    W[0] = cmul(c2{bf_lo(p_cre), bf_lo(p_cim)}, c2{bf_lo(p_bre), bf_lo(p_bim)});
    W[1] = cmul(c2{bf_hi(p_cre), bf_hi(p_cim)}, c2{bf_hi(p_bre), bf_hi(p_bim)});
  }
  float mx = fmaxf(fmaxf(fabsf(W[0].r), fabsf(W[0].i)), fmaxf(fabsf(W[1].r), fabsf(W[1].i)));
  uint32_t eb = __reduce_max_sync(0xffffffffu, __float_as_uint(mx)) >> 23;
  eb = min(max(eb, 14u), 253u);
  const float sc = __uint_as_float((267u - eb) << 23);
  const float unsc = __uint_as_float((eb - 13u) << 23) * dt;
#pragma unroll
  for (int m = 0; m < 2; m++) { W[m].r *= sc; W[m].i *= sc; }

  const uint32_t st = kb + lane * 4;
  const uint32_t ld = kb + (((lane >> 3) & 1) * 8 + (lane & 7)) * 144 + (lane >> 4) * 16;
  auto putB = [&](int r, const c2& v0, const c2& v1) {
    sts32(st + r * 144, pack_h2(v0.r, v1.r));
    sts32(st + (8 + r) * 144, pack_h2(-v0.i, -v1.i));
  };
  uint32_t bf[3][8][2];
  c2 s2[2], s4[2], s6[2];
  {
    c2 z[2], p[2];
#pragma unroll
    for (int m = 0; m < 2; m++) { z[m] = zpow(a2[m], tau[m], 1.f); p[m] = W[m]; }
#pragma unroll
    for (int r = 0; r < 8; r++) {
      putB(r, p[0], p[1]);
      if (r == 2) { s2[0] = p[0]; s2[1] = p[1]; }
      if (r == 4) { s4[0] = p[0]; s4[1] = p[1]; }
      if (r == 6) { s6[0] = p[0]; s6[1] = p[1]; }
      if (r < 7) { p[0] = cmul(p[0], z[0]); p[1] = cmul(p[1], z[1]); }
    }
    __syncwarp();
#pragma unroll
    for (int k = 0; k < 8; k += 2) ldsm4(ld + k * 16, bf[0][k][0], bf[0][k][1], bf[0][k + 1][0], bf[0][k + 1][1]);
  }
  {
    c2 z[2], p[2], q[2], t2[2], t6[2];
#pragma unroll
    for (int m = 0; m < 2; m++) {
      z[m] = zpow(a2[m], tau[m], 256.f);
      p[m] = cmul(W[m], z[m]); q[m] = cmul(s4[m], z[m]); t2[m] = cmul(s2[m], z[m]); t6[m] = cmul(s6[m], z[m]);
    }
    __syncwarp();
    putB(0, p[0], p[1]); putB(1, t2[0], t2[1]); putB(2, q[0], q[1]); putB(3, t6[0], t6[1]);
#pragma unroll
    for (int r = 4; r < 8; r += 2) {
#pragma unroll
      for (int m = 0; m < 2; m++) { p[m] = cmul(p[m], z[m]); q[m] = cmul(q[m], z[m]); }
      putB(r, p[0], p[1]); putB(r + 1, q[0], q[1]);
    }
    __syncwarp();
#pragma unroll
    for (int k = 0; k < 8; k += 2) ldsm4(ld + k * 16, bf[1][k][0], bf[1][k][1], bf[1][k + 1][0], bf[1][k + 1][1]);
    p[0] = cmul(p[0], z[0]); p[1] = cmul(p[1], z[1]);
    __syncwarp();
#pragma unroll
    for (int r = 0; r < 5; r++) {
      putB(r, p[0], p[1]);
      if (r < 4) { p[0] = cmul(p[0], z[0]); p[1] = cmul(p[1], z[1]); }
    }
    __syncwarp();
#pragma unroll
    for (int k = 0; k < 8; k += 2) ldsm4(ld + k * 16, bf[2][k][0], bf[2][k][1], bf[2][k + 1][0], bf[2][k + 1][1]);
  }
  {
    c2 z[2], p[2], y[2], y2[2];
#pragma unroll
    for (int m = 0; m < 2; m++) {
      z[m] = zpow(a2[m], tau[m], 8.f); p[m] = z[m];
      y[m] = zpow(a2[m], tau[m], 64.f); y2[m] = cmul(y[m], y[m]);
    }
    __syncwarp();
    sts32(st, 0x3C003C00u); sts32(st + 8 * 144, 0u);
#pragma unroll
    for (int r = 1; r < 8; r++) {
      sts32(st + r * 144, pack_h2(p[0].r, p[1].r));
      sts32(st + (8 + r) * 144, pack_h2(p[0].i, p[1].i));
      if (r < 7) { p[0] = cmul(p[0], z[0]); p[1] = cmul(p[1], z[1]); }
    }
    sts128(kb + 2304 + lane * 16, pack_h2(y[0].r, y[1].r), pack_h2(y[0].i, y[1].i), pack_h2(y2[0].r, y2[1].r),
           pack_h2(y2[0].i, y2[1].i));
    __syncwarp();
  }
  float acc[2][3][4];
#pragma unroll
  for (int i = 0; i < 2; i++)
#pragma unroll
    for (int j = 0; j < 3; j++) acc[i][j][0] = acc[i][j][1] = acc[i][j][2] = acc[i][j][3] = 0.f;
#pragma unroll
  for (int k = 0; k < 8; k += 2) {
    uint32_t R[2], I[2];
    ldsm4(ld + k * 16, R[0], I[0], R[1], I[1]);
#pragma unroll
    for (int h = 0; h < 2; h++) {
      const uint4 mu = lds128(kb + 2304 + ((k + h) * 4 + c) * 16);
      const uint32_t r1 = hfnma2(I[h], mu.y, hmul2(R[h], mu.x)), i1 = hfma2(I[h], mu.x, hmul2(R[h], mu.y));
      const uint32_t r2 = hfnma2(I[h], mu.w, hmul2(R[h], mu.z)), i2 = hfma2(I[h], mu.z, hmul2(R[h], mu.w));
      const uint32_t r3 = hfnma2(i1, mu.w, hmul2(r1, mu.z)), i3 = hfma2(i1, mu.z, hmul2(r1, mu.w));
#pragma unroll
      for (int nb = 0; nb < 3; nb++) {
        mma16816(acc[0][nb], R[h], r1, I[h], i1, bf[nb][k + h][0], bf[nb][k + h][1]);
        mma16816(acc[1][nb], r2, r3, i2, i3, bf[nb][k + h][0], bf[nb][k + h][1]);
      }
    }
  }
  __syncwarp();
#pragma unroll
  for (int q = 0; q < 4; q++) {
    const int j = 8 * q + g, mb = q >> 1, o = (q & 1) * 2;
    sts64f(kb + (8 * j + 2 * c) * 4, acc[mb][0][o] * unsc, acc[mb][0][o + 1] * unsc);
    const int i1 = c < 2 ? 256 + 4 * j + 2 * c : 384 + 64 * (c - 2) + 2 * j;
    sts64f(kb + i1 * 4, acc[mb][1][o] * unsc, acc[mb][1][o + 1] * unsc);
    if (c < 2) sts64f(kb + (512 + 4 * j + 2 * c) * 4, acc[mb][2][o] * unsc, acc[mb][2][o + 1] * unsc);
  }
  if (lane == 2) sts64f(kb + 640 * 4, acc[0][2][0] * unsc, fabsf(unsc) * (64.f * 1.5f * 16384.f));
}

__device__ __forceinline__ int src_dense(int l) {
  int s = l < 256 ? l : 128 + (l >> 1) + (l & (l >> 1) & 1);
  s = (l == 510) ? 642 : s;
  return (l < 0 || l > 510) ? 641 : s;
}
__device__ __forceinline__ int src_seg2(int k, int off) {
  const int v = 16 * k + off;
  return (v < 512 || v > 1024) ? 641 : 384 + ((v - 512) >> 2);
}
__device__ __forceinline__ int src_seg3(int k, int off) {
  const int n8 = 2 * k + off - 128;
  const int s = n8 == 128 ? 640 : 512 + 4 * (n8 & 31) + (n8 >> 5);
  return k < 64 ? 641 : s;
}

template <int J0, int NJ>
__device__ __forceinline__ void conv_item(uint32_t sb, int ch, int dglob, int lane) {
  const int g = lane >> 2, c = lane & 3, rho = lane & 7, t0 = (lane >> 3) & 1, t1 = lane >> 4;
  float acc[NJ][4];
#pragma unroll
  for (int j = 0; j < NJ; j++) acc[j][0] = acc[j][1] = acc[j][2] = acc[j][3] = 0.f;
  const uint32_t tb = sb + SM_T + ch * TCH + (g - 2 * c) * 4;
  const uint32_t ub = sb + SM_U + ch * 32 + (8 + 8 * t1) * 160;
  {
    constexpr int M0 = J0 - 3 > 0 ? J0 - 3 : 0, NB = J0 + NJ - M0;
    uint32_t am[4];
#pragma unroll
    for (int q = 0; q < 4; q++) am[q] = lds32(tb + (16 + 128 * q - 8) * 4);
#pragma unroll 1
    for (int e = 0; e < 8; e++) {
      const int r = rho - e;
      const uint32_t ua = ub + r * 160 + ((t0 ^ ((r >> 2) & 1)) << 4) + M0 * 1280;
      const uint32_t ta = tb + (16 + 16 * e) * 4;
      uint32_t b[NB][2], a0[4], a1[4];
#pragma unroll
      for (int q = 0; q < 4; q++) { a0[q] = lds32(ta + q * 512); a1[q] = lds32(ta + q * 512 + 32); }
#pragma unroll
      for (int m = 0; m < NB; m += 2) {
        if (m + 1 < NB) ldsm4(ua + m * 1280, b[m][0], b[m][1], b[m + 1][0], b[m + 1][1]);
        else ldsm2(ua + m * 1280, b[m][0], b[m][1]);
      }
#pragma unroll
      for (int q = 3; q >= 0; q--) {
#pragma unroll
        for (int j = 0; j < NJ; j++) {
          const int m = J0 + j - q - M0;
          if (m >= 0) mma16816(acc[j], a0[q], a1[q], am[q], a0[q], b[m][0], b[m][1]);
        }
        am[q] = a1[q];
      }
    }
    if (J0 + NJ > 4) {
      constexpr int JS = J0 > 4 ? J0 : 4, N4 = J0 + NJ - JS;
      const uint32_t ua = ub + rho * 160 + ((t0 ^ (rho >> 2)) << 4) + (JS - 4) * 1280;
      const uint32_t a0 = lds32(tb + (16 + 512) * 4);
#pragma unroll
      for (int m = 0; m < N4; m += 2) {
        uint32_t b0, b1, b2, b3;
        if (m + 1 < N4) {
          ldsm4(ua + m * 1280, b0, b1, b2, b3);
          mma16816(acc[JS - J0 + m + 1], a0, 0u, am[3], a0, b2, b3);
        } else {
          ldsm2(ua + m * 1280, b0, b1);
        }
        mma16816(acc[JS - J0 + m], a0, 0u, am[3], a0, b0, b1);
      }
    }
  }
  const uint32_t wb = sb + SM_W + ch * WCH + rho * 16;
#pragma unroll
  for (int p = 0; p < 2; p++) {
    const int IMIN = p == 0 ? -1 : 0;
    const int I0 = J0 - 8 > IMIN ? J0 - 8 : IMIN, I1 = J0 + NJ - 5;
    if (I1 >= I0) {
      const uint32_t ps = p == 0 ? W5_PS : W3_PS;
      const uint32_t base = wb + (p == 0 ? W5_OFF + 9 * 16 : W3_OFF + 16);
      const uint32_t x4 = base + t0 * ps + t1 * 128, x2 = base + ps + t0 * 128 - 16;
      uint32_t bt[5][2];
#pragma unroll
      for (int dl = 4; dl <= 8; dl++) {
        if (dl <= J0 + NJ - 1 - I0) {
          bt[dl - 4][0] = lds32(tb + (544 + 96 * p + 8 * dl - 24) * 4);
          bt[dl - 4][1] = lds32(tb + (544 + 96 * p + 48 + 8 * dl - 24) * 4);
        }
      }
#pragma unroll
      for (int i = I0; i <= I1; i += 2) {
        uint32_t e[2], o[2], om[2];
        if (i + 1 <= I1) { ldsm4t(x4 + i * 128, e[0], o[0], e[1], o[1]); ldsm2t(x2 + i * 128, om[0], om[1]); }
        else { ldsm2t(x4 + i * 128, e[0], o[0]); ldsm1t(x2 + i * 128, om[0]); }
#pragma unroll
        for (int h = 0; h < 2; h++) {
          if (i + h <= I1) {
#pragma unroll
            for (int j = 0; j < NJ; j++) {
              const int dl = J0 + j - i - h;
              if (dl >= 4 && dl <= 8) mma16816(acc[j], e[h], o[h], om[h], e[h], bt[dl - 4][0], bt[dl - 4][1]);
            }
          }
        }
      }
    }
  }
  if (J0 + NJ > 8) {
    constexpr int I1 = J0 + NJ - 9;
    uint32_t bt[8][2];
#pragma unroll
    for (int dl = 8; dl <= J0 + NJ - 1; dl++) {
      bt[dl - 8][0] = lds32(tb + (736 + 8 * dl - 56) * 4);
      bt[dl - 8][1] = lds32(tb + (736 + 72 + 8 * dl - 56) * 4);
    }
    const uint32_t x4 = wb + W9_OFF + t1 * (W7_OFF - W9_OFF) + t0 * W9_PS;
#pragma unroll
    for (int i = 0; i <= I1; i++) {
      uint32_t a0, a1, a2, a3;
      ldsm4t(x4 + i * 128, a0, a1, a2, a3);
#pragma unroll
      for (int j = 0; j < NJ; j++) {
        const int dl = J0 + j - i;
        if (dl >= 8) mma16816(acc[j], a0, a1, a2, a3, bt[dl - 8][0], bt[dl - 8][1]);
      }
    }
    const uint32_t k1024 = lds32(sb + SM_T + ch * TCH + 880 * 4);
    const uint32_t bd = g == 2 * c ? (k1024 & 0xffffu) : (g == 2 * c + 1 ? (k1024 << 16) : 0u);
    constexpr int JS = J0 > 8 ? J0 : 8, N8 = J0 + NJ - JS;
    const uint32_t xm = wb + WM_OFF + t0 * W9_PS + t1 * 128 + (JS - 8) * 128;
#pragma unroll
    for (int m = 0; m < N8; m += 2) {
      uint32_t a0, a1, a2, a3;
      if (m + 1 < N8) {
        ldsm4t(xm + m * 128, a0, a1, a2, a3);
        mma1688(acc[JS - J0 + m + 1], a2, a3, bd);
      } else {
        ldsm2t(xm + m * 128, a0, a1);
      }
      mma1688(acc[JS - J0 + m], a0, a1, bd);
    }
  }
  const float inv = ldsf(sb + SM_T + ch * TCH + 881 * 4);
  const int f = (dglob >> 1) & 3;
  uint32_t* o0 = g_s + (size_t)(J0 * D_ + dglob) * 64 + ((2 * c) ^ f) * 8 + g;
  uint32_t* o1 = g_s + (size_t)(J0 * D_ + dglob) * 64 + ((2 * c + 1) ^ f) * 8 + g;
#pragma unroll
  for (int j = 0; j < NJ; j++) {
    o0[j * D_ * 64] = pack_b2(acc[j][0] * inv, acc[j][2] * inv);
    o1[j * D_ * 64] = pack_b2(acc[j][1] * inv, acc[j][3] * inv);
  }
}

__global__ void __launch_bounds__(NTHREADS, 1)
s4_ffn_kernel(const __grid_constant__ CUtensorMap tmX, const __grid_constant__ CUtensorMap tmW1,
              const __grid_constant__ CUtensorMap tmW2, const __grid_constant__ CUtensorMap tmU,
              const __grid_constant__ CUtensorMap tmXe, const __grid_constant__ CUtensorMap tmO, const Params P) {
  extern __shared__ uint8_t smem_raw[];
  const int tid = threadIdx.x, lane = tid & 31;
  const int warp = __shfl_sync(0xffffffffu, tid >> 5, 0);
  const uint32_t sb = __shfl_sync(0xffffffffu, ((uint32_t)__cvta_generic_to_shared(smem_raw) + 1023u) & ~1023u, 0);

  int cta;
  if (P.use_smid) {
    uint32_t s; asm("mov.u32 %0, %%smid;" : "=r"(s));
    int gpc, idx;
    if (s < 64) { gpc = (s & 15) >> 1; idx = (s >> 4) * 2 + (s & 1); }
    else if (s < 120) { const int t = s - 64, q = t / 14; gpc = 1 + ((t - q * 14) >> 1); idx = 8 + q * 2 + (s & 1); }
    else { gpc = 0; idx = 8 + (s - 124); }
    cta = (s >= 120 && s < 124) ? -1 : (2 * gpc + (idx & 1)) * 8 + (idx >> 1);
  } else {
    cta = blockIdx.x;
  }
  cta = __shfl_sync(0xffffffffu, cta, 0);
  if (cta < 0) {
    if (tid == 0) {
      const unsigned old = atomicAdd(&g_cnt[C_CHK * 32], 1u);
      poll_flag(&g_cnt[C_CHK * 32], (old / gridDim.x + 1) * gridDim.x);
    }
    return;
  }
  const int mt = cta >> 3, ns = cta & 7;

  uint32_t p_are = 0, p_aim = 0, p_bre = 0, p_bim = 0, p_cre = 0, p_cim = 0;
  float logdt = 0.f;
  unsigned chk = 0;
  if (warp < 15) {
    const int o = (cta * 15 + warp) * 64 + lane * 2;
    p_are = ldg32(P.are + o); p_aim = ldg32(P.aim + o); p_bre = ldg32(P.bre + o);
    p_bim = ldg32(P.bim + o); p_cre = ldg32(P.cre + o); p_cim = ldg32(P.cim + o);
    logdt = __bfloat162float(P.logdt[cta * 5 + warp / 3]);
    if (tid == 12 * 32) chk = atomicAdd(&g_cnt[C_CHK * 32], 1u);
  } else if (elect_one()) {
    for (int i = 0; i < 3; i++) { mbar_init(sb + B_FULL1 + 8 * i, 1); mbar_init(sb + B_EMPTY1 + 8 * i, 2); mbar_init(sb + B_HST + 8 * i, 8); }
    for (int i = 0; i < 8; i++) { mbar_init(sb + B_FULL2 + 8 * i, 1); mbar_init(sb + B_EMPTY2 + 8 * i, 2); }
    mbar_init(sb + B_W2LD, 1); mbar_init(sb + B_ULD, 1); mbar_init(sb + B_ST1RD, 1);
    mbar_init(sb + B_G1DONE, 1); mbar_init(sb + B_CVDONE, 1); mbar_init(sb + B_XS, 1);
    asm volatile("fence.mbarrier_init.release.cluster;" ::: "memory");
    fence_async_smem();
    tm_prefetch(&tmX); tm_prefetch(&tmW1); tm_prefetch(&tmW2);
  }
  __syncthreads();

  if (warp == 15) {
    if (elect_one()) {
#pragma unroll
      for (int k = 0; k < 3; k++) {
        mbar_expect(sb + B_FULL1 + 8 * k, G1_STAGE);
        tma2d(sb + k * G1_STAGE, &tmX, k * 64, mt * 128, sb + B_FULL1 + 8 * k);
        tma3d(sb + k * G1_STAGE + 16384, &tmW1, 0, k * 64, ns * 3, sb + B_FULL1 + 8 * k);
      }
      bulk_prefetch(P.x + (size_t)cta * 16 * D_, 16 * D_ * 2);
      bulk_prefetch(P.w1 + (size_t)cta * 5 * F_, 5 * F_ * 2);
      tm_prefetch(&tmU); tm_prefetch(&tmXe); tm_prefetch(&tmO);
      mbar_wait(sb + B_FULL1, 0);
      TS1(0);
      mbar_expect(sb + B_W2LD, 15360);
#pragma unroll
      for (int u = 0; u < 3; u++) tma3d(sb + SM_W2ST + u * 5120, &tmW2, 0, (mt * 3 + u) * 32, ns * 5, sb + B_W2LD);
#pragma unroll
      for (int k = 3; k < 10; k++) {
        const int s = k % 3;
        mbar_wait(sb + B_EMPTY1 + 8 * s, ((k / 3) & 1) ^ 1);
        mbar_expect(sb + B_FULL1 + 8 * s, G1_STAGE);
        tma2d(sb + s * G1_STAGE, &tmX, k * 64, mt * 128, sb + B_FULL1 + 8 * s);
        tma3d(sb + s * G1_STAGE + 16384, &tmW1, 0, k * 64, ns * 3, sb + B_FULL1 + 8 * s);
      }
      mbar_wait(sb + B_G1DONE, 0);
      fence_async();
      const unsigned ep = lds32(sb + SM_EPOCH);
      const uint8_t* hp = g_h + (size_t)mt * 24 * 16384;
      const uint8_t* wp = g_w2r + (size_t)ns * 24 * 10240;
#pragma unroll
      for (int q = 0; q < 4; q++) {
        mbar_expect(sb + B_FULL2 + 8 * q, 26624);
        bulk_g2s(sb + g2b(q), wp + q * 3 * 10240, 10240, sb + B_FULL2 + 8 * q);
      }
      poll_flag(&g_cnt[(C_F3 + mt * 3) * 32], ep * 8);
      fence_async();
      TS1(1);
#pragma unroll
      for (int q = 0; q < 4; q++) {
        if (q == 3) mbar_wait(sb + B_ST1RD, 0);
        bulk_g2s(sb + g2a(q), hp + q * 3 * 16384, 16384, sb + B_FULL2 + 8 * q);
      }
      mbar_wait(sb + B_CVDONE, 0);
      fence_async();
#pragma unroll
      for (int q = 4; q < 24; q++) {
        const int s = q & 7, kbl = q >> 3, kb = 3 * s + kbl;
        if (q >= 8) {
          if (s == 0) { poll_flag(&g_cnt[(C_F3 + mt * 3 + kbl) * 32], ep * 8); fence_async(); }
          mbar_wait(sb + B_EMPTY2 + 8 * s, (kbl & 1) ^ 1);
        }
        mbar_expect(sb + B_FULL2 + 8 * s, 26624);
        bulk_g2s(sb + g2a(s), hp + kb * 16384, 16384, sb + B_FULL2 + 8 * s);
        bulk_g2s(sb + g2b(s), wp + kb * 10240, 10240, sb + B_FULL2 + 8 * s);
      }
      poll_flag(&g_cnt[(C_F4 + ns) * 32], ep * 16);
      fence_async();
      TS1(2);
      mbar_wait(sb + B_EMPTY2, 0);
      mbar_wait(sb + B_EMPTY2 + 8, 0);
      mbar_expect(sb + B_XS, 40960);
      tma2d(sb + SM_XT, &tmXe, ns * 80, mt * 128, sb + B_XS);
      bulk_g2s(sb + SM_S, g_s + (size_t)(mt * D_ + ns * 80) * 64, 20480, sb + B_XS);
      TS1(3);
    }
    return;
  }

  {
    const float dt = bf_round(expf(logdt));
    TS(0);
    kgen_warp(sb + SM_W + warp * KBUF, lane, p_are, p_aim, p_bre, p_bim, p_cre, p_cim, dt);
  }
  TS(1);
  bar_sync(1, 480);
  TS(2);
  const int g = lane >> 2, c = lane & 3;

  if (warp < 8) {
    float acc[96];
    const int wg = warp >> 2;
#pragma unroll
    for (int k = 0; k < 10; k++) {
      const int s = k % 3;
      mbar_wait(sb + B_FULL1 + 8 * s, (k / 3) & 1);
      const uint64_t da = mkdesc(sb + s * G1_STAGE + wg * 8192, 16, 1024, 1);
      const uint64_t db = mkdesc(sb + s * G1_STAGE + 16384, 8192, 1024, 1);
      wg_fence();
#pragma unroll
      for (int kk = 0; kk < 4; kk++) wgmma_n192(acc, da + kk * 2, db + kk * 128, k + kk);
      wg_commit();
      if (k > 0 && k < 8) {
        wg_wait<1>();
        if ((tid & 127) == 0) mbar_arrive(sb + B_EMPTY1 + 8 * ((k - 1) % 3));
      }
    }
    wg_wait<0>();
    TS(3);
    bar_sync(5, 480);
    if (tid == 0) mbar_arrive(sb + B_G1DONE);
    TS(4);
    const float2 s0 = lds64f(sb + SM_ST + (warp * 16 + g) * 8), s1 = lds64f(sb + SM_ST + (warp * 16 + 8 + g) * 8);
    const int rho = lane & 7;
    const uint32_t sa = sb + SM_HST + (warp * 16 + ((lane >> 3) & 1) * 8 + rho) * 128;
#pragma unroll
    for (int k3 = 0; k3 < 3; k3++) {
#pragma unroll
      for (int jj = 0; jj < 8; jj += 2) {
        uint32_t r[4];
#pragma unroll
        for (int h = 0; h < 2; h++) {
          const int j = k3 * 8 + jj + h;
          const float2 cs = lds64f(sb + SM_CS + (8 * j + 2 * c) * 4);
          const float h0 = fmaf(acc[4 * j], s0.x, s0.y * cs.x), h1 = fmaf(acc[4 * j + 1], s0.x, s0.y * cs.y);
          const float h2 = fmaf(acc[4 * j + 2], s1.x, s1.y * cs.x), h3 = fmaf(acc[4 * j + 3], s1.x, s1.y * cs.y);
          r[2 * h] = pack_b2(fmaf(h0, tanh_fast(h0), h0), fmaf(h1, tanh_fast(h1), h1));
          r[2 * h + 1] = pack_b2(fmaf(h2, tanh_fast(h2), h2), fmaf(h3, tanh_fast(h3), h3));
        }
        stsm4(sa + k3 * 16384 + (((jj + (lane >> 4)) ^ rho) << 4), r[0], r[1], r[2], r[3]);
      }
      fence_async_smem();
      __syncwarp();
      if (lane == 0) {
        mbar_arrive(sb + B_HST + 8 * k3);
        if (warp == 4 + k3) {
          mbar_wait(sb + B_HST + 8 * k3, 0);
          bulk_s2g(g_h + (size_t)(mt * 24 + ns * 3 + k3) * 16384, sb + SM_HST + k3 * 16384, 16384);
          bulk_commit();
        }
      }
      __syncwarp();
    }
    TS(5);
    if (warp >= 4 && warp < 7) {
      if (lane == 0) {
        if (warp == 5) { bulk_wait0_read(); mbar_arrive(sb + B_ST1RD); }
        bulk_wait0();
        red_release(&g_cnt[(C_F3 + mt * 3 + warp - 4) * 32]);
      }
      __syncwarp();
    }
  } else {
    const int at = tid - 256;
    if (warp < 12) {
      const int tok = (warp - 8) * 4 + (lane >> 3), l8 = lane & 7;
      const uint4* xr = reinterpret_cast<const uint4*>(P.x + (size_t)(cta * 16 + tok) * D_) + l8;
      uint4 v[10];
#pragma unroll
      for (int i = 0; i < 10; i++) v[i] = __ldg(xr + 8 * i);
      float sum = 0.f;
#pragma unroll
      for (int i = 0; i < 10; i++)
        sum += ((bf_lo(v[i].x) + bf_hi(v[i].x)) + (bf_lo(v[i].y) + bf_hi(v[i].y))) +
               ((bf_lo(v[i].z) + bf_hi(v[i].z)) + (bf_lo(v[i].w) + bf_hi(v[i].w)));
      sum += __shfl_xor_sync(0xffffffffu, sum, 1);
      sum += __shfl_xor_sync(0xffffffffu, sum, 2);
      sum += __shfl_xor_sync(0xffffffffu, sum, 4);
      const float mean = sum * (1.f / D_);
      float q0 = 0.f, q1 = 0.f;
#pragma unroll
      for (int i = 0; i < 10; i++) {
        const uint32_t w[4] = {v[i].x, v[i].y, v[i].z, v[i].w};
#pragma unroll
        for (int k = 0; k < 4; k++) {
          const float d0 = bf_lo(w[k]) - mean, d1 = bf_hi(w[k]) - mean;
          q0 = fmaf(d0, d0, q0); q1 = fmaf(d1, d1, q1);
        }
      }
      float sq = q0 + q1;
      sq += __shfl_xor_sync(0xffffffffu, sq, 1);
      sq += __shfl_xor_sync(0xffffffffu, sq, 2);
      sq += __shfl_xor_sync(0xffffffffu, sq, 4);
      const float mb = bf_round(mean);
      const float rs = 1.f / bf_round(sqrtf(bf_round(bf_round(sq * (1.f / D_)) + 1e-5f)));
      const float nb = -mb * rs;
      if (l8 == 0) g_stats[cta * 16 + tok] = make_float2(0.5f * rs, 0.5f * nb);
      const uint32_t sa = sb + SM_U + (((tok >> 1) & 1) * 8 + (tok >> 2) * 2 + (tok & 1)) * LN_PITCH + l8 * 16;
#pragma unroll
      for (int i = 0; i < 10; i++)
        sts128(sa + i * 128, pack_h2(fmaf(bf_lo(v[i].x), rs, nb), fmaf(bf_hi(v[i].x), rs, nb)),
               pack_h2(fmaf(bf_lo(v[i].y), rs, nb), fmaf(bf_hi(v[i].y), rs, nb)),
               pack_h2(fmaf(bf_lo(v[i].z), rs, nb), fmaf(bf_hi(v[i].z), rs, nb)),
               pack_h2(fmaf(bf_lo(v[i].w), rs, nb), fmaf(bf_hi(v[i].w), rs, nb)));
      bar_sync(2, 128);
      const uint32_t la = sb + SM_U + (lane & 15) * LN_PITCH + ((warp - 8) * 20 + (lane >> 4)) * 16;
      uint2* uo = reinterpret_cast<uint2*>(g_uT + (size_t)cta * D_ * 32 + ((warp - 8) * 160 + g) * 32 +
                                           ((c ^ (((cta >> 2) & 1) * 2)) * 8));
#pragma unroll
      for (int i = 0; i < 10; i++) {
        uint32_t r0, r1, r2, r3;
        ldsm4t(la + i * 32, r0, r1, r2, r3);
        uo[i * 64] = make_uint2(r0, r1);
        uo[i * 64 + 32] = make_uint2(r2, r3);
      }
      fence_async_smem();
    } else {
      const int t = at - 128;
      {
        const __nv_bfloat16* wp = P.w1 + (size_t)(mt * 40) * F_ + ns * 192 + 2 * t;
        float c0 = 0.f, c1 = 0.f;
#pragma unroll
        for (int b = 0; b < 2; b++) {
          uint32_t w[20];
#pragma unroll
          for (int i = 0; i < 20; i++) w[i] = ldg32(wp + (size_t)(b * 20 + i) * F_);
#pragma unroll
          for (int i = 0; i < 20; i++) { c0 += bf_lo(w[i]); c1 += bf_hi(w[i]); }
        }
        *reinterpret_cast<float2*>(g_csp + mt * F_ + ns * 192 + 2 * t) = make_float2(c0, c1);
      }
#pragma unroll 1
      for (int ch = 0; ch < 5; ch++) {
        const uint32_t k0 = sb + SM_W + ch * 3 * KBUF;
        const float dsk = __bfloat162float(P.dskip[cta * 5 + ch]);
        const float bound = ldsf(k0 + 641 * 4) + ldsf(k0 + KBUF + 641 * 4) + ldsf(k0 + 2 * KBUF + 641 * 4) + fabsf(dsk);
        const uint32_t eb = min(max(__float_as_uint(bound) >> 23, 14u), 253u);
        const float sc = __uint_as_float((267u - eb) << 23);
        const uint32_t kh = sb + SM_KH + ch * KH_CH;
#pragma unroll
        for (int it = 0; it < 2; it++) {
          const int qd = t + it * 96;
          if (qd < 160) {
            const uint4 a = lds128(k0 + qd * 16), b = lds128(k0 + KBUF + qd * 16), d = lds128(k0 + 2 * KBUF + qd * 16);
            float x0 = __uint_as_float(a.x) + __uint_as_float(b.x) + __uint_as_float(d.x);
            const float x1 = __uint_as_float(a.y) + __uint_as_float(b.y) + __uint_as_float(d.y);
            const float x2 = __uint_as_float(a.z) + __uint_as_float(b.z) + __uint_as_float(d.z);
            const float x3 = __uint_as_float(a.w) + __uint_as_float(b.w) + __uint_as_float(d.w);
            if (qd == 0) x0 += dsk;
            sts64(kh + qd * 8, pack_h2(x0 * sc, x1 * sc), pack_h2(x2 * sc, x3 * sc));
          } else if (qd == 160) {
            float k2048 = 0.f, k510 = 0.f, k1024 = 0.f;
#pragma unroll
            for (int w = 0; w < 3; w++) {
              k2048 += ldsf(k0 + w * KBUF + 640 * 4);
              k510 += ldsf(k0 + w * KBUF + 383 * 4) - ldsf(k0 + w * KBUF + 384 * 4);
              k1024 += ldsf(k0 + w * KBUF + 512 * 4);
            }
            sts64(kh + 1280, pack_h2(k2048 * sc, 0.f), pack_h2(k510 * sc, 0.f));
            sts64(sb + SM_T + ch * TCH + 880 * 4, pack_h2(k1024 * sc, 0.f), (eb - 13u) << 23);
          }
        }
      }
      if (tid == 12 * 32) {
        mbar_wait(sb + B_W2LD, 0);
        bulk_s2g(g_w2r + (size_t)ns * 24 * 10240 + mt * 15360, sb + SM_W2ST, 15360);
        bulk_commit();
      }
      __syncwarp();
    }
    TS(3);
    bar_sync(4, 224);
    if (warp == 12) {
      if (lane == 0) {
        const unsigned ep = chk / gridDim.x + 1;
        sts32(sb + SM_EPOCH, ep);
        bulk_wait0();
        red_release(&g_cnt[C_F2 * 32]);
        TS1(4);
        poll_flag(&g_cnt[C_F2 * 32], ep * 128);
        fence_async();
        mbar_expect(sb + B_ULD, 136 * 160);
        tma2d(sb + SM_U, &tmU, cta * 80, -8, sb + B_ULD);
      }
      __syncwarp();
    } else {
      const int t = warp < 12 ? at : at - 32;
#pragma unroll 1
      for (int w = t; w < 880; w += 192) {
        int lo, hi;
        if (w < 544) { lo = src_dense(w - 16); hi = src_dense(w - 17); }
        else if (w < 736) {
          const int kd = (w - 544) / 48, x = 24 + (w - 544) - kd * 48, off = (kd & 1) * 8 + (kd >> 1) * 4;
          lo = src_seg2(x, off); hi = src_seg2(x - 1, off);
        } else {
          const int kd = (w - 736) / 72, x = 56 + (w - 736) - kd * 72;
          lo = src_seg3(x, 2 - kd); hi = src_seg3(x - 1, 2 - kd);
        }
#pragma unroll
        for (int ch = 0; ch < 5; ch++)
          sts32(sb + SM_T + ch * TCH + w * 4,
                lds16(sb + SM_KH + ch * KH_CH + lo * 2) | (lds16(sb + SM_KH + ch * KH_CH + hi * 2) << 16));
      }
    }
    TS(5);
    bar_sync(3, 224);
    {
      float csum = 0.f;
      if (at < 192) {
        float p[16];
#pragma unroll
        for (int i = 0; i < 16; i++) p[i] = __ldcg(g_csp + i * F_ + ns * 192 + at);
#pragma unroll
        for (int i = 0; i < 16; i++) csum += p[i];
        sts32(sb + SM_CS + at * 4, __float_as_uint(csum));
      }
      if (at >= 96) {
        const float2 st = __ldcg(g_stats + mt * 128 + at - 96);
        sts64f(sb + SM_ST + (at - 96) * 8, st.x, st.y);
      }
    }
    mbar_wait(sb + B_ULD, 0);
    TS(6);
    {
      const int eta = at - 18;
      uint32_t ua[3];
#pragma unroll
      for (int k = 0; k < 3; k++) {
        const int e = max(eta - 1 + k, -16) + 16;
        ua[k] = sb + SM_U + (e >> 1) * 160 + (((e & 1) ^ ((e >> 3) & 1)) << 4);
      }
      const int e5 = eta + 18, e3 = eta + 2, e9 = eta + 2, e7 = eta + 1;
      const uint32_t o5 = sb + SM_W + W5_OFF + (e5 & 1) * W5_PS + (e5 >> 1) * 16;
      const uint32_t o3 = sb + SM_W + W3_OFF + (e3 & 1) * W3_PS + (e3 >> 1) * 16;
      const uint32_t o9 = sb + SM_W + W9_OFF + (e9 & 1) * W9_PS + (e9 >> 1) * 16;
      const uint32_t o7 = sb + SM_W + W7_OFF + (e7 & 1) * W9_PS + (e7 >> 1) * 16;
      const uint32_t om = sb + SM_W + WM_OFF + (eta & 1) * W9_PS + (eta >> 1) * 16;
#pragma unroll 1
      for (int ch = 0; ch < 5; ch++) {
        const uint4 pa = lds128(ua[0] + ch * 32), pb = lds128(ua[1] + ch * 32), pc = lds128(ua[2] + ch * 32);
        const uint32_t E[9] = {pa.y, pa.z, pa.w, pb.x, pb.y, pb.z, pb.w, pc.x, pc.y};
        uint32_t O[8], w3[6], w5[4];
#pragma unroll
        for (int i = 0; i < 8; i++) O[i] = __byte_perm(E[i], E[i + 1], 0x5432);
#pragma unroll
        for (int i = 0; i < 6; i++) w3[i] = hadd2(hadd2(O[i], O[i + 1]), E[i + 1]);
#pragma unroll
        for (int i = 0; i < 4; i++) w5[i] = hadd2(w3[i + 2], hadd2(E[i + 2], E[i + 4]));
        if (eta < 192) {
          sts128(o5 + ch * WCH, w5[0], w5[1], w5[2], w5[3]);
          if (eta >= -2) sts128(o3 + ch * WCH, w3[0], w3[1], w3[2], w3[3]);
        }
        if (eta >= -2 && eta < 128) {
          uint32_t w7[4], w9[4], wm[4];
#pragma unroll
          for (int i = 0; i < 4; i++) {
            w7[i] = hadd2(w5[i], hadd2(O[i + 1], O[i + 4]));
            w9[i] = hadd2(w7[i], hadd2(E[i + 1], E[i + 5]));
            wm[i] = hadd2(O[i + 1], E[i + 1]);
          }
          if (eta < 126) sts128(o9 + ch * WCH, w9[0], w9[1], w9[2], w9[3]);
          if (eta >= -1 && eta < 127) sts128(o7 + ch * WCH, w7[0], w7[1], w7[2], w7[3]);
          if (eta >= 0) sts128(om + ch * WCH, wm[0], wm[1], wm[2], wm[3]);
        }
      }
    }
    TS(7);
    bar_sync(5, 480);
  }

  TS(8);
  if (warp >= 8 && warp < 12) conv_item<8, 8>(sb, warp - 8, cta * 5 + warp - 8, lane);
  else if (warp >= 12 || warp == 7) conv_item<0, 8>(sb, warp & 3, cta * 5 + (warp & 3), lane);
  else if (warp == 0) conv_item<13, 3>(sb, 4, cta * 5 + 4, lane);
  else if (warp == 1) conv_item<9, 4>(sb, 4, cta * 5 + 4, lane);
  else if (warp == 2) conv_item<5, 4>(sb, 4, cta * 5 + 4, lane);
  else if (warp == 3) conv_item<0, 5>(sb, 4, cta * 5 + 4, lane);
  fence_async_smem();
  TS(9);
  bar_sync(6, 480);
  if (warp >= 8) {
    if (tid == 8 * 32) mbar_arrive(sb + B_CVDONE);
    if (tid == 12 * 32) red_release(&g_cnt[(C_F4 + (cta >> 4)) * 32]);
    return;
  }
  TS(10);

  {
    float acc[40];
    const int wg = warp >> 2;
#pragma unroll 1
    for (int kbl = 0; kbl < 3; kbl++) {
#pragma unroll
      for (int s = 0; s < 8; s++) {
        mbar_wait(sb + B_FULL2 + 8 * s, kbl & 1);
        const uint64_t da = mkdesc(sb + g2a(s) + wg * 8192, 16, 1024, 1);
        const uint64_t db = mkdesc(sb + g2b(s), 1024, 256, 3);
        wg_fence();
#pragma unroll
        for (int kk = 0; kk < 4; kk++) wgmma_n80(acc, da + kk * 2, db + (kk >> 1) * 320 + (kk & 1) * 32, kbl + s + kk);
        wg_commit();
        wg_wait<1>();
        if ((tid & 127) == 0 && (kbl + s) > 0) mbar_arrive(sb + B_EMPTY2 + 8 * ((s + 7) & 7));
      }
    }
    wg_wait<0>();
    TS(11);
    mbar_wait(sb + B_XS, 0);
    TS(12);
    const int rho = lane & 7;
    const uint32_t xa = sb + SM_XT + (warp * 16 + ((lane >> 3) & 1) * 8 + rho) * 160 + (((lane >> 4) ^ (rho >> 2)) << 4);
    const uint32_t sa = sb + SM_S + c * 512 + ((warp ^ c) << 5) + g * 4;
    const bool sw = g >= 4;
#pragma unroll
    for (int jj = 0; jj < 10; jj += 2) {
      uint32_t x0, x1, x2, x3, p[4];
      ldsm4(xa + jj * 16, x0, x1, x2, x3);
#pragma unroll
      for (int h = 0; h < 2; h++) {
        const int j = jj + h;
        const uint32_t w0 = lds32(sa + j * 2048), w1 = lds32(sa + j * 2048 + 256);
        const float h0 = 0.5f * acc[4 * j], h1 = 0.5f * acc[4 * j + 1], h2 = 0.5f * acc[4 * j + 2], h3 = 0.5f * acc[4 * j + 3];
        p[2 * h] = pack_b2(fmaf(h0, tanh_fast(h0), h0) * bf_lo(w0), fmaf(h1, tanh_fast(h1), h1) * bf_lo(w1));
        p[2 * h + 1] = pack_b2(fmaf(h2, tanh_fast(h2), h2) * bf_hi(w0), fmaf(h3, tanh_fast(h3), h3) * bf_hi(w1));
      }
      stsm4(xa + jj * 16, badd2(x0, sw ? p[2] : p[0]), badd2(x1, sw ? p[3] : p[1]), badd2(x2, sw ? p[0] : p[2]),
            badd2(x3, sw ? p[1] : p[3]));
    }
    fence_async_smem();
    __syncwarp();
    if (lane == 0) {
      tma2d_store(&tmO, sb + SM_XT + warp * 2560, ns * 80, mt * 128 + warp * 16);
      bulk_commit();
      TS1(13);
      bulk_wait0_read();
      TS1(14);
    }
  }
}

typedef CUresult (*EncodeFn)(CUtensorMap*, CUtensorMapDataType, cuuint32_t, void*, const cuuint64_t*, const cuuint64_t*,
                             const cuuint32_t*, const cuuint32_t*, CUtensorMapInterleave, CUtensorMapSwizzle,
                             CUtensorMapL2promotion, CUtensorMapFloatOOBfill);

void make_map(EncodeFn enc, CUtensorMap* m, void* base, int rank, const cuuint64_t* dims, const cuuint64_t* strides,
              const cuuint32_t* box, CUtensorMapSwizzle sw) {
  const cuuint32_t es[3] = {1, 1, 1};
  enc(m, CU_TENSOR_MAP_DATA_TYPE_BFLOAT16, rank, base, dims, strides, box, es, CU_TENSOR_MAP_INTERLEAVE_NONE, sw,
      CU_TENSOR_MAP_L2_PROMOTION_L2_128B, CU_TENSOR_MAP_FLOAT_OOB_FILL_NONE);
}

}

extern "C" void kernel_launch(void* const* d_in, const int* in_sizes, int n_in, void* d_out, int out_size) {
  (void)in_sizes; (void)n_in; (void)out_size;
  static EncodeFn enc = nullptr;
  static int nsm = 0;
  static void* p_uT = nullptr;
  if (!enc) {
    void* fn = nullptr;
    cudaDriverEntryPointQueryResult q;
    cudaGetDriverEntryPoint("cuTensorMapEncodeTiled", &fn, cudaEnableDefault, &q);
    enc = (EncodeFn)fn;
    int dev = 0;
    cudaGetDevice(&dev);
    cudaDeviceGetAttribute(&nsm, cudaDevAttrMultiProcessorCount, dev);
    cudaGetSymbolAddress(&p_uT, g_uT);
    cudaFuncSetAttribute(s4_ffn_kernel, cudaFuncAttributeMaxDynamicSharedMemorySize, SMEM_BYTES);
  }
  void* x = d_in[0];
  void* w1 = d_in[10];
  void* w2 = d_in[11];
  CUtensorMap tmX, tmW1, tmW2, tmU, tmXe, tmO;
  {
    const cuuint64_t d[2] = {D_, L_}, s[1] = {D_ * 2};
    const cuuint32_t b0[2] = {64, 128}, b1[2] = {80, 128}, b2[2] = {80, 16};
    make_map(enc, &tmX, x, 2, d, s, b0, CU_TENSOR_MAP_SWIZZLE_128B);
    make_map(enc, &tmXe, x, 2, d, s, b1, CU_TENSOR_MAP_SWIZZLE_NONE);
    make_map(enc, &tmO, d_out, 2, d, s, b2, CU_TENSOR_MAP_SWIZZLE_NONE);
  }
  {
    const cuuint64_t d[3] = {64, D_, F_ / 64}, s[2] = {F_ * 2, 128};
    const cuuint32_t b[3] = {64, 64, 3};
    make_map(enc, &tmW1, w1, 3, d, s, b, CU_TENSOR_MAP_SWIZZLE_128B);
  }
  {
    const cuuint64_t d[3] = {16, F_, D_ / 16}, s[2] = {D_ * 2, 32};
    const cuuint32_t b[3] = {16, 32, 5};
    make_map(enc, &tmW2, w2, 3, d, s, b, CU_TENSOR_MAP_SWIZZLE_32B);
  }
  {
    const cuuint64_t d[2] = {D_ * 16, 128}, s[1] = {D_ * 32};
    const cuuint32_t b[2] = {80, 136};
    make_map(enc, &tmU, p_uT, 2, d, s, b, CU_TENSOR_MAP_SWIZZLE_NONE);
  }
  Params P;
  P.x = (const __nv_bfloat16*)d_in[0];
  P.are = (const __nv_bfloat16*)d_in[1]; P.aim = (const __nv_bfloat16*)d_in[2];
  P.bre = (const __nv_bfloat16*)d_in[3]; P.bim = (const __nv_bfloat16*)d_in[4];
  P.cre = (const __nv_bfloat16*)d_in[5]; P.cim = (const __nv_bfloat16*)d_in[6];
  P.logdt = (const __nv_bfloat16*)d_in[7]; P.dskip = (const __nv_bfloat16*)d_in[8];
  P.w1 = (const __nv_bfloat16*)d_in[10];
  P.use_smid = (nsm == 132);
  s4_ffn_kernel<<<P.use_smid ? 132 : 128, NTHREADS, SMEM_BYTES>>>(tmX, tmW1, tmW2, tmU, tmXe, tmO, P);
}
```

```cpp
#include <cuda_runtime.h>
#include <cuda_bf16.h>
#include <cuda_fp16.h>
#include <cuda.h>
#include <stdint.h>

namespace {

constexpr int L_ = 2048, D_ = 640, F_ = 1536;
constexpr int NTHREADS = 512;
#define TX 500
#define TW2 1500
#define TG1 2800
#define TH 1500
#define LN_W0 8
#define RING 6
#define STAG_K 0
#define ALIGN_STEP 14
constexpr int T_X = TX, T_W2 = TW2, T_G1 = TG1, T_H = TH;

constexpr uint32_t SB = 1024;
constexpr uint32_t G1_STAGE = 40960;
constexpr uint32_t G2_SLOT = 26624;
constexpr uint32_t Y_ = SB + 3 * G1_STAGE;
constexpr uint32_t WCH = 4352, W7_OFF = 2176, W_PS = 272;
constexpr uint32_t SM_W = Y_;
constexpr uint32_t KBUF = 2624;
constexpr uint32_t SM_U = Y_ + 39936;
constexpr uint32_t UCH = 4352;
constexpr uint32_t SM_T = SM_U + 22528;
constexpr uint32_t TCH = 8192, NTW = 1632, CP_W = 1640;
constexpr uint32_t SM_CS = SM_T + 5 * TCH;
constexpr uint32_t SM_ST = SM_CS + 3072;
constexpr uint32_t SM_BAR = SM_ST + 1024;
constexpr uint32_t SMEM_BYTES = SM_BAR + 512 - SB;
static_assert(SMEM_BYTES <= 232448, "smem");
static_assert(SM_W + 5 * WCH + 4 * 4352 <= SM_U && SM_W + 15 * KBUF <= SM_U && (SM_T % 256) == 0 && (SM_U % 1024) == 0, "smem alias");
static_assert(SB + 8 * G2_SLOT <= SM_CS, "ring");
constexpr uint32_t B_FULL1 = SM_BAR, B_FULL2 = SM_BAR + 24, B_W2LD = SM_BAR + 88, B_ULD = SM_BAR + 96;
constexpr uint32_t B_CST = SM_BAR + 104, B_H12 = SM_BAR + 112, B_SOK = SM_BAR + 120, B_XS = SM_BAR + 128;
constexpr uint32_t B_XROW = SM_BAR + 144;
constexpr uint32_t B_EMPTY1 = SM_BAR + 152, B_EMPTY2 = SM_BAR + 176;
constexpr uint32_t B_HST = SM_BAR + 240;
constexpr uint32_t B_PREP = SM_BAR + 264;
constexpr uint32_t SM_EPOCH = SM_BAR + 272, SM_LNST = SM_BAR + 384;
constexpr uint32_t SM_HST = SB;
constexpr uint32_t SM_XT = SB;
constexpr uint32_t SM_S = SB + G2_SLOT;

struct Scratch {
  uint8_t h[16 * 24 * 16384];
  uint8_t uT[D_ * 128 * 32];
  uint8_t w2r[8 * 24 * 10240];
  uint32_t s[D_ * 16 * 64];
  float2 stats[L_];
  uint4 cs[F_];
  unsigned cnt[72 * 32];
};
__device__ __align__(1024) Scratch g_scr;
constexpr int C_CHK = 0, C_U = 1, C_CS = 2, C_S = 8, C_H = 16, C_AL = 48;

struct IdxTab { uint32_t v[NTW]; };
constexpr int kpos(int v) {
  if (v < 256) return v;
  if (v < 512) return 128 + (v >> 1);
  if (v < 1024) return 256 + (v >> 2);
  return 512 + 68 * ((v >> 3) & 1) + ((v - 1024) >> 4);
}
constexpr int bf16_lag(int l) {
  const int sh = l < 256 ? 0 : (l < 512 ? 1 : (l < 1024 ? 2 : 3));
  if (sh == 0) return l;
  const int q = l >> sh, r = l & ((1 << sh) - 1), half = 1 << (sh - 1);
  return (q + ((r > half || (r == half && (q & 1))) ? 1 : 0)) << sh;
}
constexpr int tap_src(int w, int hi) {
  if (w < 1120) {
    const int l = w - 32 - hi;
    return (l < 0 || l > 1028) ? -1 : kpos(bf16_lag(l));
  }
  const int r = w - 1120, n = 63 - ((r & 255) >> 2);
  const int lag = 1024 + 16 * n - 256 * ((r >> 1) & 1) - 64 * (r & 1) - 16 * hi + ((r >> 8) ? 8 : 16);
  return lag < 1032 ? -1 : kpos(lag);
}
constexpr IdxTab make_idx() {
  IdxTab t{};
  for (int w = 0; w < (int)NTW; w++) {
    const int lo = tap_src(w, 0), hi = tap_src(w, 1);
    const int p = lo >= 0 ? lo : (hi >= 0 ? hi : 256);
    const uint32_t sel = (lo >= 0 ? 0x10u : 0x44u) | (hi < 0 ? 0x4400u : (hi == p ? 0x1000u : 0x3200u));
    t.v[w] = (uint32_t)((p < 256 ? 32 + p : (int)CP_W + p - 256) * 4) | (sel << 16);
  }
  return t;
}
__device__ __align__(128) const IdxTab g_idx = make_idx();
#define TSX(r, i)
#define TS(i)
#define TS1(i)

struct Params {
  const __nv_bfloat16 *are, *aim, *bre, *bim, *cre, *cim, *logdt, *dskip, *w1;
  Scratch* scr;
  const uint32_t* idx;
  uint32_t zero;
};

__device__ __forceinline__ bool elect_one() {
  uint32_t p;
  asm volatile("{.reg .pred P; elect.sync _|P, 0xffffffff; selp.u32 %0,1,0,P;}" : "=r"(p));
  return p;
}
__device__ __forceinline__ void mbar_init(uint32_t a, uint32_t c) {
  asm volatile("mbarrier.init.shared::cta.b64 [%0], %1;" ::"r"(a), "r"(c) : "memory");
}
__device__ __forceinline__ void mbar_expect(uint32_t a, uint32_t b) {
  asm volatile("mbarrier.arrive.expect_tx.shared::cta.b64 _, [%0], %1;" ::"r"(a), "r"(b) : "memory");
}
__device__ __forceinline__ void mbar_arrive(uint32_t a) {
  asm volatile("mbarrier.arrive.shared::cta.b64 _, [%0];" ::"r"(a) : "memory");
}
__device__ __forceinline__ void mbar_wait(uint32_t a, uint32_t ph) {
  asm volatile(
      "{.reg .pred p; .reg .u32 n; mov.u32 n, 0;\n"
      "LW%=: mbarrier.try_wait.parity.shared::cta.b64 p, [%0], %1;\n"
      "@p bra LD%=; add.u32 n, n, 1; setp.lt.u32 p, n, 200000; @p bra LW%=;\n"
      "LD%=: }" ::"r"(a), "r"(ph) : "memory");
}
__device__ __forceinline__ void bar_sync(int id, int n) { asm volatile("bar.sync %0, %1;" ::"r"(id), "r"(n) : "memory"); }
__device__ __forceinline__ void bar_arrive(int id, int n) { asm volatile("bar.arrive %0, %1;" ::"r"(id), "r"(n) : "memory"); }
__device__ __forceinline__ void fence_async() { asm volatile("fence.proxy.async.global;" ::: "memory"); }
__device__ __forceinline__ void fence_async_smem() { asm volatile("fence.proxy.async.shared::cta;" ::: "memory"); }
__device__ __forceinline__ void red_release(unsigned* p) {
  asm volatile("red.release.gpu.global.add.u32 [%0], 1;" ::"l"(p) : "memory");
}
__device__ __forceinline__ void poll_flag(const unsigned* p, unsigned target) {
  for (int n = 0; n < 100000; n++) {
    unsigned v;
    asm volatile("ld.acquire.gpu.global.u32 %0, [%1];" : "=r"(v) : "l"(p) : "memory");
    if ((int)(v - target) >= 0) break;
  }
}
__device__ __forceinline__ void bulk_g2s(uint32_t dst, const void* src, uint32_t bytes, uint32_t bar) {
  asm volatile("cp.async.bulk.shared::cluster.global.mbarrier::complete_tx::bytes [%0], [%1], %2, [%3];" ::"r"(dst),
               "l"(src), "r"(bytes), "r"(bar) : "memory");
}
__device__ __forceinline__ void bulk_s2g(void* dst, uint32_t src, uint32_t bytes) {
  asm volatile("cp.async.bulk.global.shared::cta.bulk_group [%0], [%1], %2;" ::"l"(dst), "r"(src), "r"(bytes) : "memory");
}
__device__ __forceinline__ void bulk_prefetch(const void* src, uint32_t bytes) {
  asm volatile("cp.async.bulk.prefetch.L2.global [%0], %1;" ::"l"(src), "r"(bytes) : "memory");
}
__device__ __forceinline__ void bulk_commit() { asm volatile("cp.async.bulk.commit_group;" ::: "memory"); }
__device__ __forceinline__ void bulk_wait0() { asm volatile("cp.async.bulk.wait_group 0;" ::: "memory"); }
__device__ __forceinline__ void bulk_wait0_read() { asm volatile("cp.async.bulk.wait_group.read 0;" ::: "memory"); }
__device__ __forceinline__ void tma2d(uint32_t dst, const CUtensorMap* m, int c0, int c1, uint32_t bar) {
  asm volatile("cp.async.bulk.tensor.2d.shared::cluster.global.mbarrier::complete_tx::bytes [%0], [%1, {%3, %4}], [%2];"
               ::"r"(dst), "l"(m), "r"(bar), "r"(c0), "r"(c1) : "memory");
}
__device__ __forceinline__ void tma3d(uint32_t dst, const CUtensorMap* m, int c0, int c1, int c2, uint32_t bar) {
  asm volatile("cp.async.bulk.tensor.3d.shared::cluster.global.mbarrier::complete_tx::bytes [%0], [%1, {%3, %4, %5}], [%2];"
               ::"r"(dst), "l"(m), "r"(bar), "r"(c0), "r"(c1), "r"(c2) : "memory");
}
__device__ __forceinline__ void tma5d(uint32_t dst, const CUtensorMap* m, int c2, uint32_t bar) {
  asm volatile("cp.async.bulk.tensor.5d.shared::cluster.global.mbarrier::complete_tx::bytes [%0], [%1, {0, 0, %3, 0, 0}], [%2];"
               ::"r"(dst), "l"(m), "r"(bar), "r"(c2) : "memory");
}
__device__ __forceinline__ void tma2d_store(const CUtensorMap* m, uint32_t src, int c0, int c1) {
  asm volatile("cp.async.bulk.tensor.2d.global.shared::cta.bulk_group [%0, {%2, %3}], [%1];" ::"l"(m), "r"(src), "r"(c0),
               "r"(c1) : "memory");
}
__device__ __forceinline__ void tm_prefetch(const CUtensorMap* m) {
  asm volatile("prefetch.tensormap [%0];" ::"l"(m) : "memory");
}
__device__ __forceinline__ uint64_t mkdesc(uint32_t addr, uint32_t lbo, uint32_t sbo, uint32_t mode) {
  return (uint64_t)((addr & 0x3FFFF) >> 4) | ((uint64_t)(lbo >> 4) << 16) | ((uint64_t)(sbo >> 4) << 32) |
         ((uint64_t)mode << 62);
}
__device__ __forceinline__ void wg_fence() { asm volatile("wgmma.fence.sync.aligned;" ::: "memory"); }
__device__ __forceinline__ void wg_commit() { asm volatile("wgmma.commit_group.sync.aligned;" ::: "memory"); }
template <int N> __device__ __forceinline__ void wg_wait() {
  asm volatile("wgmma.wait_group.sync.aligned %0;" ::"n"(N) : "memory");
}
__device__ __forceinline__ void wgmma_n192(float (&d)[96], uint64_t da, uint64_t db, int acc) {
  asm volatile(
      "{.reg .pred p; setp.ne.b32 p, %98, 0;\n"
      "wgmma.mma_async.sync.aligned.m64n192k16.f32.bf16.bf16 {"
      "%0,%1,%2,%3,%4,%5,%6,%7,%8,%9,%10,%11,%12,%13,%14,%15,"
      "%16,%17,%18,%19,%20,%21,%22,%23,%24,%25,%26,%27,%28,%29,%30,%31,"
      "%32,%33,%34,%35,%36,%37,%38,%39,%40,%41,%42,%43,%44,%45,%46,%47,"
      "%48,%49,%50,%51,%52,%53,%54,%55,%56,%57,%58,%59,%60,%61,%62,%63,"
      "%64,%65,%66,%67,%68,%69,%70,%71,%72,%73,%74,%75,%76,%77,%78,%79,"
      "%80,%81,%82,%83,%84,%85,%86,%87,%88,%89,%90,%91,%92,%93,%94,%95"
      "}, %96, %97, p, 1, 1, 0, 1;}\n"
      :
        "+f"(d[0]), "+f"(d[1]), "+f"(d[2]), "+f"(d[3]), "+f"(d[4]), "+f"(d[5]), "+f"(d[6]), "+f"(d[7]),
        "+f"(d[8]), "+f"(d[9]), "+f"(d[10]), "+f"(d[11]), "+f"(d[12]), "+f"(d[13]), "+f"(d[14]), "+f"(d[15]),
        "+f"(d[16]), "+f"(d[17]), "+f"(d[18]), "+f"(d[19]), "+f"(d[20]), "+f"(d[21]), "+f"(d[22]), "+f"(d[23]),
        "+f"(d[24]), "+f"(d[25]), "+f"(d[26]), "+f"(d[27]), "+f"(d[28]), "+f"(d[29]), "+f"(d[30]), "+f"(d[31]),
        "+f"(d[32]), "+f"(d[33]), "+f"(d[34]), "+f"(d[35]), "+f"(d[36]), "+f"(d[37]), "+f"(d[38]), "+f"(d[39]),
        "+f"(d[40]), "+f"(d[41]), "+f"(d[42]), "+f"(d[43]), "+f"(d[44]), "+f"(d[45]), "+f"(d[46]), "+f"(d[47]),
        "+f"(d[48]), "+f"(d[49]), "+f"(d[50]), "+f"(d[51]), "+f"(d[52]), "+f"(d[53]), "+f"(d[54]), "+f"(d[55]),
        "+f"(d[56]), "+f"(d[57]), "+f"(d[58]), "+f"(d[59]), "+f"(d[60]), "+f"(d[61]), "+f"(d[62]), "+f"(d[63]),
        "+f"(d[64]), "+f"(d[65]), "+f"(d[66]), "+f"(d[67]), "+f"(d[68]), "+f"(d[69]), "+f"(d[70]), "+f"(d[71]),
        "+f"(d[72]), "+f"(d[73]), "+f"(d[74]), "+f"(d[75]), "+f"(d[76]), "+f"(d[77]), "+f"(d[78]), "+f"(d[79]),
        "+f"(d[80]), "+f"(d[81]), "+f"(d[82]), "+f"(d[83]), "+f"(d[84]), "+f"(d[85]), "+f"(d[86]), "+f"(d[87]),
        "+f"(d[88]), "+f"(d[89]), "+f"(d[90]), "+f"(d[91]), "+f"(d[92]), "+f"(d[93]), "+f"(d[94]), "+f"(d[95])
      : "l"(da), "l"(db), "r"(acc));
}

__device__ __forceinline__ void wgmma_n80(float (&d)[40], uint64_t da, uint64_t db, int acc) {
  asm volatile(
      "{.reg .pred p; setp.ne.b32 p, %42, 0;\n"
      "wgmma.mma_async.sync.aligned.m64n80k16.f32.bf16.bf16 {"
      "%0,%1,%2,%3,%4,%5,%6,%7,%8,%9,%10,%11,%12,%13,%14,%15,"
      "%16,%17,%18,%19,%20,%21,%22,%23,%24,%25,%26,%27,%28,%29,%30,%31,"
      "%32,%33,%34,%35,%36,%37,%38,%39"
      "}, %40, %41, p, 1, 1, 0, 1;}\n"
      :
        "+f"(d[0]), "+f"(d[1]), "+f"(d[2]), "+f"(d[3]), "+f"(d[4]), "+f"(d[5]), "+f"(d[6]), "+f"(d[7]),
        "+f"(d[8]), "+f"(d[9]), "+f"(d[10]), "+f"(d[11]), "+f"(d[12]), "+f"(d[13]), "+f"(d[14]), "+f"(d[15]),
        "+f"(d[16]), "+f"(d[17]), "+f"(d[18]), "+f"(d[19]), "+f"(d[20]), "+f"(d[21]), "+f"(d[22]), "+f"(d[23]),
        "+f"(d[24]), "+f"(d[25]), "+f"(d[26]), "+f"(d[27]), "+f"(d[28]), "+f"(d[29]), "+f"(d[30]), "+f"(d[31]),
        "+f"(d[32]), "+f"(d[33]), "+f"(d[34]), "+f"(d[35]), "+f"(d[36]), "+f"(d[37]), "+f"(d[38]), "+f"(d[39])
      : "l"(da), "l"(db), "r"(acc));
}

__device__ __forceinline__ void wgmma_n192_rs(float (&d)[96], const uint32_t (&a)[4], uint64_t db) {
  asm volatile(
      "wgmma.mma_async.sync.aligned.m64n192k16.f32.bf16.bf16 {"
      "%0,%1,%2,%3,%4,%5,%6,%7,%8,%9,%10,%11,%12,%13,%14,%15,"
      "%16,%17,%18,%19,%20,%21,%22,%23,%24,%25,%26,%27,%28,%29,%30,%31,"
      "%32,%33,%34,%35,%36,%37,%38,%39,%40,%41,%42,%43,%44,%45,%46,%47,"
      "%48,%49,%50,%51,%52,%53,%54,%55,%56,%57,%58,%59,%60,%61,%62,%63,"
      "%64,%65,%66,%67,%68,%69,%70,%71,%72,%73,%74,%75,%76,%77,%78,%79,"
      "%80,%81,%82,%83,%84,%85,%86,%87,%88,%89,%90,%91,%92,%93,%94,%95"
      "}, {%96,%97,%98,%99}, %100, 1, 1, 1, 0;\n"
      :
        "+f"(d[0]), "+f"(d[1]), "+f"(d[2]), "+f"(d[3]), "+f"(d[4]), "+f"(d[5]), "+f"(d[6]), "+f"(d[7]),
        "+f"(d[8]), "+f"(d[9]), "+f"(d[10]), "+f"(d[11]), "+f"(d[12]), "+f"(d[13]), "+f"(d[14]), "+f"(d[15]),
        "+f"(d[16]), "+f"(d[17]), "+f"(d[18]), "+f"(d[19]), "+f"(d[20]), "+f"(d[21]), "+f"(d[22]), "+f"(d[23]),
        "+f"(d[24]), "+f"(d[25]), "+f"(d[26]), "+f"(d[27]), "+f"(d[28]), "+f"(d[29]), "+f"(d[30]), "+f"(d[31]),
        "+f"(d[32]), "+f"(d[33]), "+f"(d[34]), "+f"(d[35]), "+f"(d[36]), "+f"(d[37]), "+f"(d[38]), "+f"(d[39]),
        "+f"(d[40]), "+f"(d[41]), "+f"(d[42]), "+f"(d[43]), "+f"(d[44]), "+f"(d[45]), "+f"(d[46]), "+f"(d[47]),
        "+f"(d[48]), "+f"(d[49]), "+f"(d[50]), "+f"(d[51]), "+f"(d[52]), "+f"(d[53]), "+f"(d[54]), "+f"(d[55]),
        "+f"(d[56]), "+f"(d[57]), "+f"(d[58]), "+f"(d[59]), "+f"(d[60]), "+f"(d[61]), "+f"(d[62]), "+f"(d[63]),
        "+f"(d[64]), "+f"(d[65]), "+f"(d[66]), "+f"(d[67]), "+f"(d[68]), "+f"(d[69]), "+f"(d[70]), "+f"(d[71]),
        "+f"(d[72]), "+f"(d[73]), "+f"(d[74]), "+f"(d[75]), "+f"(d[76]), "+f"(d[77]), "+f"(d[78]), "+f"(d[79]),
        "+f"(d[80]), "+f"(d[81]), "+f"(d[82]), "+f"(d[83]), "+f"(d[84]), "+f"(d[85]), "+f"(d[86]), "+f"(d[87]),
        "+f"(d[88]), "+f"(d[89]), "+f"(d[90]), "+f"(d[91]), "+f"(d[92]), "+f"(d[93]), "+f"(d[94]), "+f"(d[95])
      : "r"(a[0]), "r"(a[1]), "r"(a[2]), "r"(a[3]), "l"(db));
}

template <int N> __device__ __forceinline__ void cv_rs(float (&d)[64], const uint32_t (&a)[4], uint64_t db, int acc);
template <> __device__ __forceinline__ void cv_rs<128>(float (&d)[64], const uint32_t (&a)[4], uint64_t db, int acc) {
  asm volatile(
      "{.reg .pred p; setp.ne.b32 p, %69, 0;\n"
      "wgmma.mma_async.sync.aligned.m64n128k16.f32.f16.f16 {"
      "%0,%1,%2,%3,%4,%5,%6,%7,%8,%9,%10,%11,%12,%13,%14,%15,"
      "%16,%17,%18,%19,%20,%21,%22,%23,%24,%25,%26,%27,%28,%29,%30,%31,"
      "%32,%33,%34,%35,%36,%37,%38,%39,%40,%41,%42,%43,%44,%45,%46,%47,"
      "%48,%49,%50,%51,%52,%53,%54,%55,%56,%57,%58,%59,%60,%61,%62,%63"
      "}, {%64,%65,%66,%67}, %68, p, 1, 1, 0;}\n"
      :
        "+f"(d[0]), "+f"(d[1]), "+f"(d[2]), "+f"(d[3]), "+f"(d[4]), "+f"(d[5]), "+f"(d[6]), "+f"(d[7]),
        "+f"(d[8]), "+f"(d[9]), "+f"(d[10]), "+f"(d[11]), "+f"(d[12]), "+f"(d[13]), "+f"(d[14]), "+f"(d[15]),
        "+f"(d[16]), "+f"(d[17]), "+f"(d[18]), "+f"(d[19]), "+f"(d[20]), "+f"(d[21]), "+f"(d[22]), "+f"(d[23]),
        "+f"(d[24]), "+f"(d[25]), "+f"(d[26]), "+f"(d[27]), "+f"(d[28]), "+f"(d[29]), "+f"(d[30]), "+f"(d[31]),
        "+f"(d[32]), "+f"(d[33]), "+f"(d[34]), "+f"(d[35]), "+f"(d[36]), "+f"(d[37]), "+f"(d[38]), "+f"(d[39]),
        "+f"(d[40]), "+f"(d[41]), "+f"(d[42]), "+f"(d[43]), "+f"(d[44]), "+f"(d[45]), "+f"(d[46]), "+f"(d[47]),
        "+f"(d[48]), "+f"(d[49]), "+f"(d[50]), "+f"(d[51]), "+f"(d[52]), "+f"(d[53]), "+f"(d[54]), "+f"(d[55]),
        "+f"(d[56]), "+f"(d[57]), "+f"(d[58]), "+f"(d[59]), "+f"(d[60]), "+f"(d[61]), "+f"(d[62]), "+f"(d[63])
      : "r"(a[0]), "r"(a[1]), "r"(a[2]), "r"(a[3]), "l"(db), "r"(acc));
}

template <> __device__ __forceinline__ void cv_rs<112>(float (&d)[64], const uint32_t (&a)[4], uint64_t db, int acc) {
  asm volatile(
      "{.reg .pred p; setp.ne.b32 p, %61, 0;\n"
      "wgmma.mma_async.sync.aligned.m64n112k16.f32.f16.f16 {"
      "%0,%1,%2,%3,%4,%5,%6,%7,%8,%9,%10,%11,%12,%13,%14,%15,"
      "%16,%17,%18,%19,%20,%21,%22,%23,%24,%25,%26,%27,%28,%29,%30,%31,"
      "%32,%33,%34,%35,%36,%37,%38,%39,%40,%41,%42,%43,%44,%45,%46,%47,"
      "%48,%49,%50,%51,%52,%53,%54,%55"
      "}, {%56,%57,%58,%59}, %60, p, 1, 1, 0;}\n"
      :
        "+f"(d[0]), "+f"(d[1]), "+f"(d[2]), "+f"(d[3]), "+f"(d[4]), "+f"(d[5]), "+f"(d[6]), "+f"(d[7]),
        "+f"(d[8]), "+f"(d[9]), "+f"(d[10]), "+f"(d[11]), "+f"(d[12]), "+f"(d[13]), "+f"(d[14]), "+f"(d[15]),
        "+f"(d[16]), "+f"(d[17]), "+f"(d[18]), "+f"(d[19]), "+f"(d[20]), "+f"(d[21]), "+f"(d[22]), "+f"(d[23]),
        "+f"(d[24]), "+f"(d[25]), "+f"(d[26]), "+f"(d[27]), "+f"(d[28]), "+f"(d[29]), "+f"(d[30]), "+f"(d[31]),
        "+f"(d[32]), "+f"(d[33]), "+f"(d[34]), "+f"(d[35]), "+f"(d[36]), "+f"(d[37]), "+f"(d[38]), "+f"(d[39]),
        "+f"(d[40]), "+f"(d[41]), "+f"(d[42]), "+f"(d[43]), "+f"(d[44]), "+f"(d[45]), "+f"(d[46]), "+f"(d[47]),
        "+f"(d[48]), "+f"(d[49]), "+f"(d[50]), "+f"(d[51]), "+f"(d[52]), "+f"(d[53]), "+f"(d[54]), "+f"(d[55])
      : "r"(a[0]), "r"(a[1]), "r"(a[2]), "r"(a[3]), "l"(db), "r"(acc));
}

template <> __device__ __forceinline__ void cv_rs<96>(float (&d)[64], const uint32_t (&a)[4], uint64_t db, int acc) {
  asm volatile(
      "{.reg .pred p; setp.ne.b32 p, %53, 0;\n"
      "wgmma.mma_async.sync.aligned.m64n96k16.f32.f16.f16 {"
      "%0,%1,%2,%3,%4,%5,%6,%7,%8,%9,%10,%11,%12,%13,%14,%15,"
      "%16,%17,%18,%19,%20,%21,%22,%23,%24,%25,%26,%27,%28,%29,%30,%31,"
      "%32,%33,%34,%35,%36,%37,%38,%39,%40,%41,%42,%43,%44,%45,%46,%47"
      "}, {%48,%49,%50,%51}, %52, p, 1, 1, 0;}\n"
      :
        "+f"(d[0]), "+f"(d[1]), "+f"(d[2]), "+f"(d[3]), "+f"(d[4]), "+f"(d[5]), "+f"(d[6]), "+f"(d[7]),
        "+f"(d[8]), "+f"(d[9]), "+f"(d[10]), "+f"(d[11]), "+f"(d[12]), "+f"(d[13]), "+f"(d[14]), "+f"(d[15]),
        "+f"(d[16]), "+f"(d[17]), "+f"(d[18]), "+f"(d[19]), "+f"(d[20]), "+f"(d[21]), "+f"(d[22]), "+f"(d[23]),
        "+f"(d[24]), "+f"(d[25]), "+f"(d[26]), "+f"(d[27]), "+f"(d[28]), "+f"(d[29]), "+f"(d[30]), "+f"(d[31]),
        "+f"(d[32]), "+f"(d[33]), "+f"(d[34]), "+f"(d[35]), "+f"(d[36]), "+f"(d[37]), "+f"(d[38]), "+f"(d[39]),
        "+f"(d[40]), "+f"(d[41]), "+f"(d[42]), "+f"(d[43]), "+f"(d[44]), "+f"(d[45]), "+f"(d[46]), "+f"(d[47])
      : "r"(a[0]), "r"(a[1]), "r"(a[2]), "r"(a[3]), "l"(db), "r"(acc));
}

template <> __device__ __forceinline__ void cv_rs<80>(float (&d)[64], const uint32_t (&a)[4], uint64_t db, int acc) {
  asm volatile(
      "{.reg .pred p; setp.ne.b32 p, %45, 0;\n"
      "wgmma.mma_async.sync.aligned.m64n80k16.f32.f16.f16 {"
      "%0,%1,%2,%3,%4,%5,%6,%7,%8,%9,%10,%11,%12,%13,%14,%15,"
      "%16,%17,%18,%19,%20,%21,%22,%23,%24,%25,%26,%27,%28,%29,%30,%31,"
      "%32,%33,%34,%35,%36,%37,%38,%39"
      "}, {%40,%41,%42,%43}, %44, p, 1, 1, 0;}\n"
      :
        "+f"(d[0]), "+f"(d[1]), "+f"(d[2]), "+f"(d[3]), "+f"(d[4]), "+f"(d[5]), "+f"(d[6]), "+f"(d[7]),
        "+f"(d[8]), "+f"(d[9]), "+f"(d[10]), "+f"(d[11]), "+f"(d[12]), "+f"(d[13]), "+f"(d[14]), "+f"(d[15]),
        "+f"(d[16]), "+f"(d[17]), "+f"(d[18]), "+f"(d[19]), "+f"(d[20]), "+f"(d[21]), "+f"(d[22]), "+f"(d[23]),
        "+f"(d[24]), "+f"(d[25]), "+f"(d[26]), "+f"(d[27]), "+f"(d[28]), "+f"(d[29]), "+f"(d[30]), "+f"(d[31]),
        "+f"(d[32]), "+f"(d[33]), "+f"(d[34]), "+f"(d[35]), "+f"(d[36]), "+f"(d[37]), "+f"(d[38]), "+f"(d[39])
      : "r"(a[0]), "r"(a[1]), "r"(a[2]), "r"(a[3]), "l"(db), "r"(acc));
}

template <> __device__ __forceinline__ void cv_rs<64>(float (&d)[64], const uint32_t (&a)[4], uint64_t db, int acc) {
  asm volatile(
      "{.reg .pred p; setp.ne.b32 p, %37, 0;\n"
      "wgmma.mma_async.sync.aligned.m64n64k16.f32.f16.f16 {"
      "%0,%1,%2,%3,%4,%5,%6,%7,%8,%9,%10,%11,%12,%13,%14,%15,"
      "%16,%17,%18,%19,%20,%21,%22,%23,%24,%25,%26,%27,%28,%29,%30,%31"
      "}, {%32,%33,%34,%35}, %36, p, 1, 1, 0;}\n"
      :
        "+f"(d[0]), "+f"(d[1]), "+f"(d[2]), "+f"(d[3]), "+f"(d[4]), "+f"(d[5]), "+f"(d[6]), "+f"(d[7]),
        "+f"(d[8]), "+f"(d[9]), "+f"(d[10]), "+f"(d[11]), "+f"(d[12]), "+f"(d[13]), "+f"(d[14]), "+f"(d[15]),
        "+f"(d[16]), "+f"(d[17]), "+f"(d[18]), "+f"(d[19]), "+f"(d[20]), "+f"(d[21]), "+f"(d[22]), "+f"(d[23]),
        "+f"(d[24]), "+f"(d[25]), "+f"(d[26]), "+f"(d[27]), "+f"(d[28]), "+f"(d[29]), "+f"(d[30]), "+f"(d[31])
      : "r"(a[0]), "r"(a[1]), "r"(a[2]), "r"(a[3]), "l"(db), "r"(acc));
}

__device__ __forceinline__ void cv_ss64(float (&d)[64], uint64_t da, uint64_t db) {
  asm volatile(
      "wgmma.mma_async.sync.aligned.m64n64k16.f32.f16.f16 {"
      "%0,%1,%2,%3,%4,%5,%6,%7,%8,%9,%10,%11,%12,%13,%14,%15,"
      "%16,%17,%18,%19,%20,%21,%22,%23,%24,%25,%26,%27,%28,%29,%30,%31"
      "}, %32, %33, 1, 1, 1, 1, 0;\n"
      :
        "+f"(d[0]), "+f"(d[1]), "+f"(d[2]), "+f"(d[3]), "+f"(d[4]), "+f"(d[5]), "+f"(d[6]), "+f"(d[7]),
        "+f"(d[8]), "+f"(d[9]), "+f"(d[10]), "+f"(d[11]), "+f"(d[12]), "+f"(d[13]), "+f"(d[14]), "+f"(d[15]),
        "+f"(d[16]), "+f"(d[17]), "+f"(d[18]), "+f"(d[19]), "+f"(d[20]), "+f"(d[21]), "+f"(d[22]), "+f"(d[23]),
        "+f"(d[24]), "+f"(d[25]), "+f"(d[26]), "+f"(d[27]), "+f"(d[28]), "+f"(d[29]), "+f"(d[30]), "+f"(d[31])
      : "l"(da), "l"(db));
}

__device__ __forceinline__ void cv_ss32(float (&d)[64], uint64_t da, uint64_t db) {
  asm volatile(
      "wgmma.mma_async.sync.aligned.m64n32k16.f32.f16.f16 {"
      "%0,%1,%2,%3,%4,%5,%6,%7,%8,%9,%10,%11,%12,%13,%14,%15"
      "}, %16, %17, 1, 1, 1, 1, 0;\n"
      :
        "+f"(d[0]), "+f"(d[1]), "+f"(d[2]), "+f"(d[3]), "+f"(d[4]), "+f"(d[5]), "+f"(d[6]), "+f"(d[7]),
        "+f"(d[8]), "+f"(d[9]), "+f"(d[10]), "+f"(d[11]), "+f"(d[12]), "+f"(d[13]), "+f"(d[14]), "+f"(d[15])
      : "l"(da), "l"(db));
}

__device__ __forceinline__ void wgmma_n8_ta(float (&d)[4], uint64_t da, uint64_t db) {
  asm volatile(
      "wgmma.mma_async.sync.aligned.m64n8k16.f32.bf16.bf16 {"
      "%0,%1,%2,%3"
      "}, %4, %5, 1, 1, 1, 1, 0;\n"
      :
        "+f"(d[0]), "+f"(d[1]), "+f"(d[2]), "+f"(d[3])
      : "l"(da), "l"(db));
}

__device__ __forceinline__ void mma16816(float (&d)[4], uint32_t a0, uint32_t a1, uint32_t a2, uint32_t a3, uint32_t b0,
                                         uint32_t b1) {
  asm("mma.sync.aligned.m16n8k16.row.col.f32.f16.f16.f32 {%0,%1,%2,%3},{%4,%5,%6,%7},{%8,%9},{%0,%1,%2,%3};"
      : "+f"(d[0]), "+f"(d[1]), "+f"(d[2]), "+f"(d[3]) : "r"(a0), "r"(a1), "r"(a2), "r"(a3), "r"(b0), "r"(b1));
}
__device__ __forceinline__ void mma16816b(float (&d)[4], uint32_t a0, uint32_t a1, uint32_t a2, uint32_t a3, uint32_t b0,
                                          uint32_t b1) {
  asm("mma.sync.aligned.m16n8k16.row.col.f32.bf16.bf16.f32 {%0,%1,%2,%3},{%4,%5,%6,%7},{%8,%9},{%0,%1,%2,%3};"
      : "+f"(d[0]), "+f"(d[1]), "+f"(d[2]), "+f"(d[3]) : "r"(a0), "r"(a1), "r"(a2), "r"(a3), "r"(b0), "r"(b1));
}
__device__ __forceinline__ void ldsm4(uint32_t a, uint32_t& r0, uint32_t& r1, uint32_t& r2, uint32_t& r3) {
  asm volatile("ldmatrix.sync.aligned.m8n8.x4.shared.b16 {%0,%1,%2,%3}, [%4];"
               : "=r"(r0), "=r"(r1), "=r"(r2), "=r"(r3) : "r"(a) : "memory");
}
__device__ __forceinline__ void ldsm1(uint32_t a, uint32_t& r0) {
  asm volatile("ldmatrix.sync.aligned.m8n8.x1.shared.b16 {%0}, [%1];" : "=r"(r0) : "r"(a) : "memory");
}
__device__ __forceinline__ void ldsm4t(uint32_t a, uint32_t& r0, uint32_t& r1, uint32_t& r2, uint32_t& r3) {
  asm volatile("ldmatrix.sync.aligned.m8n8.x4.trans.shared.b16 {%0,%1,%2,%3}, [%4];"
               : "=r"(r0), "=r"(r1), "=r"(r2), "=r"(r3) : "r"(a) : "memory");
}
__device__ __forceinline__ void stsm4(uint32_t a, uint32_t r0, uint32_t r1, uint32_t r2, uint32_t r3) {
  asm volatile("stmatrix.sync.aligned.m8n8.x4.shared.b16 [%0], {%1,%2,%3,%4};" ::"r"(a), "r"(r0), "r"(r1), "r"(r2), "r"(r3)
               : "memory");
}
__device__ __forceinline__ uint32_t lds32(uint32_t a) {
  uint32_t v; asm volatile("ld.shared.u32 %0, [%1];" : "=r"(v) : "r"(a) : "memory"); return v;
}
__device__ __forceinline__ float ldsf(uint32_t a) { return __uint_as_float(lds32(a)); }
__device__ __forceinline__ float2 lds64f(uint32_t a) {
  float2 v; asm volatile("ld.shared.v2.f32 {%0,%1}, [%2];" : "=f"(v.x), "=f"(v.y) : "r"(a) : "memory"); return v;
}
__device__ __forceinline__ uint2 lds64(uint32_t a) {
  uint2 v; asm volatile("ld.shared.v2.u32 {%0,%1}, [%2];" : "=r"(v.x), "=r"(v.y) : "r"(a) : "memory"); return v;
}
__device__ __forceinline__ uint4 lds128(uint32_t a) {
  uint4 v;
  asm volatile("ld.shared.v4.u32 {%0,%1,%2,%3}, [%4];" : "=r"(v.x), "=r"(v.y), "=r"(v.z), "=r"(v.w) : "r"(a) : "memory");
  return v;
}
__device__ __forceinline__ void sts32(uint32_t a, uint32_t v) { asm volatile("st.shared.u32 [%0], %1;" ::"r"(a), "r"(v) : "memory"); }
__device__ __forceinline__ void sts16(uint32_t a, uint32_t v) {
  asm volatile("st.shared.u16 [%0], %1;" ::"r"(a), "h"((uint16_t)v) : "memory");
}
__device__ __forceinline__ void sts64(uint32_t a, uint32_t x, uint32_t y) {
  asm volatile("st.shared.v2.u32 [%0], {%1,%2};" ::"r"(a), "r"(x), "r"(y) : "memory");
}
__device__ __forceinline__ void sts64f(uint32_t a, float x, float y) { sts64(a, __float_as_uint(x), __float_as_uint(y)); }
__device__ __forceinline__ void sts128(uint32_t a, uint32_t x, uint32_t y, uint32_t z, uint32_t w) {
  asm volatile("st.shared.v4.u32 [%0], {%1,%2,%3,%4};" ::"r"(a), "r"(x), "r"(y), "r"(z), "r"(w) : "memory");
}
__device__ __forceinline__ uint32_t pack_h2(float lo, float hi) {
  uint32_t r; asm("cvt.rn.f16x2.f32 %0, %1, %2;" : "=r"(r) : "f"(hi), "f"(lo)); return r;
}
__device__ __forceinline__ uint32_t pack_b2(float lo, float hi) {
  uint32_t r; asm("cvt.rn.bf16x2.f32 %0, %1, %2;" : "=r"(r) : "f"(hi), "f"(lo)); return r;
}
__device__ __forceinline__ uint32_t hadd2(uint32_t a, uint32_t b) {
  uint32_t r; asm("add.rn.f16x2 %0, %1, %2;" : "=r"(r) : "r"(a), "r"(b)); return r;
}
__device__ __forceinline__ uint32_t hmul2(uint32_t a, uint32_t b) {
  uint32_t r; asm("mul.rn.f16x2 %0, %1, %2;" : "=r"(r) : "r"(a), "r"(b)); return r;
}
__device__ __forceinline__ uint32_t hfma2(uint32_t a, uint32_t b, uint32_t c) {
  uint32_t r; asm("fma.rn.f16x2 %0, %1, %2, %3;" : "=r"(r) : "r"(a), "r"(b), "r"(c)); return r;
}
__device__ __forceinline__ uint32_t hfnma2(uint32_t a, uint32_t b, uint32_t c) {
  uint32_t r;
  asm("{.reg .b32 t; neg.f16x2 t, %1; fma.rn.f16x2 %0, t, %2, %3;}" : "=r"(r) : "r"(a), "r"(b), "r"(c));
  return r;
}
__device__ __forceinline__ uint32_t badd2(uint32_t a, uint32_t b) {
  uint32_t r; asm("add.rn.bf16x2 %0, %1, %2;" : "=r"(r) : "r"(a), "r"(b)); return r;
}
__device__ __forceinline__ float bf_lo(uint32_t v) { return __uint_as_float(v << 16); }
__device__ __forceinline__ float bf_hi(uint32_t v) { return __uint_as_float(v & 0xffff0000u); }
__device__ __forceinline__ float bf_round(float v) { return __bfloat162float(__float2bfloat16_rn(v)); }
__device__ __forceinline__ float tanh_fast(float v) { float r; asm("tanh.approx.f32 %0, %1;" : "=f"(r) : "f"(v)); return r; }
__device__ __forceinline__ float ex2_fast(float v) { float r; asm("ex2.approx.ftz.f32 %0, %1;" : "=f"(r) : "f"(v)); return r; }
__device__ __forceinline__ uint32_t ldg32(const void* p) {
  uint32_t v; asm volatile("ld.global.nc.u32 %0, [%1];" : "=r"(v) : "l"(p)); return v;
}

__device__ __forceinline__ uint32_t ldg16(const void* p) {
  uint16_t v; asm volatile("ld.global.nc.u16 %0, [%1];" : "=h"(v) : "l"(p)); return v;
}

struct c2 { float r, i; };
__device__ __forceinline__ c2 cmul(c2 a, c2 b) {
  c2 o; o.r = fmaf(-a.i, b.i, a.r * b.r); o.i = fmaf(a.r, b.i, a.i * b.r); return o;
}
__device__ __forceinline__ c2 zpow(float a2, float tau, float e) {
  const float mag = ex2_fast(a2 * e);
  const float k = __fadd_rn(fmaf(tau, e, 12582912.f), -12582912.f);
  const float ang = fmaf(tau, e, -k) * 6.283185307179586f;
  c2 o; o.r = mag * __cosf(ang); o.i = mag * __sinf(ang); return o;
}

__device__ __forceinline__ c2 csq(c2 a) { c2 o; o.r = fmaf(-a.i, a.i, a.r * a.r); o.i = (a.r + a.r) * a.i; return o; }
struct h2 { uint32_t r, i; };
__device__ __forceinline__ h2 hpack(const c2 (&v)[2]) { return h2{pack_h2(v[0].r, v[1].r), pack_h2(v[0].i, v[1].i)}; }
__device__ __forceinline__ h2 hmul(h2 a, h2 b) {
  return h2{hfnma2(a.i, b.i, hmul2(a.r, b.r)), hfma2(a.i, b.r, hmul2(a.r, b.i))};
}

__device__ __forceinline__ void kgen_warp(uint32_t kb, int lane, uint32_t p_are, uint32_t p_aim, uint32_t p_bre,
                                          uint32_t p_bim, uint32_t p_cre, uint32_t p_cim, float dt, float dsk) {
  float a2[2], tau[2];
  c2 W[2];
  {
    const float k1 = 1.4426950408889634f, k2 = 0.15915494309189535f;
    a2[0] = (dt * bf_lo(p_are)) * k1; a2[1] = (dt * bf_hi(p_are)) * k1;
    tau[0] = (dt * bf_lo(p_aim)) * k2; tau[1] = (dt * bf_hi(p_aim)) * k2;
    W[0] = cmul(c2{bf_lo(p_cre), bf_lo(p_cim)}, c2{bf_lo(p_bre), bf_lo(p_bim)});
    W[1] = cmul(c2{bf_hi(p_cre), bf_hi(p_cim)}, c2{bf_hi(p_bre), bf_hi(p_bim)});
  }
  const float mx = fmaxf(fmaxf(fabsf(W[0].r), fabsf(W[0].i)), fmaxf(fabsf(W[1].r), fabsf(W[1].i)));
  uint32_t eb = __reduce_max_sync(0xffffffffu, __float_as_uint(mx)) >> 23;
  eb = min(max(eb, 14u), 253u);
  const float sc = __uint_as_float((261u - eb) << 23);
#pragma unroll
  for (int m = 0; m < 2; m++) { W[m].r *= sc; W[m].i *= -sc; }
  if (lane == 0) sts128(kb + 2608, eb, __float_as_uint(dt), __float_as_uint(__fdividef(dsk, dt)), 0u);

  const uint32_t st = kb + lane * 4;
  const uint32_t ld = kb + (lane & 15) * 144 + (lane >> 4) * 16;
  auto put = [&](int r, h2 v) { sts32(st + r * 144, v.r); sts32(st + (8 + r) * 144, v.i); };
  uint32_t bf[3][8][2];
  auto fetch = [&](int nb) {
    __syncwarp();
#pragma unroll
    for (int k = 0; k < 8; k += 2) ldsm4(ld + k * 16, bf[nb][k][0], bf[nb][k][1], bf[nb][k + 1][0], bf[nb][k + 1][1]);
    __syncwarp();
  };
  c2 z[2];
  auto seed = [&](float sgn, float e) { z[0] = zpow(a2[0], sgn * tau[0], e); z[1] = zpow(a2[1], sgn * tau[1], e); return hpack(z); };
  auto next = [&]() { z[0] = csq(z[0]); z[1] = csq(z[1]); return hpack(z); };
  const h2 w0 = hpack(W);
  h2 w2, w4, w6;
  {
    const h2 z1 = seed(-1.f, 1.f), z2 = next(), z4 = next();
    const h2 w1 = hmul(w0, z1), w3 = hmul(w1, z2);
    w2 = hmul(w0, z2); w4 = hmul(w0, z4); w6 = hmul(w2, z4);
    put(0, w0); put(1, w1); put(2, w2); put(3, w3); put(4, w4); put(5, hmul(w1, z4)); put(6, w6); put(7, hmul(w3, z4));
    fetch(0);
  }
  {
    const h2 za = seed(-1.f, 256.f), zb = next(), zc = next();
    const h2 v1 = hmul(w0, za), v2 = hmul(w0, zb), v3 = hmul(v1, zb), w260 = hmul(w4, za);
    put(0, v1); put(1, hmul(w2, za)); put(2, w260); put(3, hmul(w6, za));
    put(4, v2); put(5, hmul(w4, zb)); put(6, v3); put(7, hmul(w260, zb));
    fetch(1);
    const h2 v4 = hmul(w0, zc);
    put(0, v4); put(2, hmul(v1, zc)); put(1, hmul(v2, zc)); put(3, hmul(v3, zc)); put(4, hmul(v4, zc));
    fetch(2);
  }
  {
    const h2 y1 = seed(1.f, 8.f), y2 = next(), y4 = next(), y8 = next();
    const h2 y3 = hmul(y1, y2);
    put(0, h2{0x3C003C00u, 0u}); put(1, y1); put(2, y2); put(3, y3); put(4, y4);
    put(5, hmul(y1, y4)); put(6, hmul(y2, y4)); put(7, hmul(y3, y4));
    sts64(kb + 2304 + lane * 8, y8.r, y8.i);
    __syncwarp();
  }
  float acc[6][4];
#pragma unroll
  for (int i = 0; i < 6; i++) acc[i][0] = acc[i][1] = acc[i][2] = acc[i][3] = 0.f;
  const uint32_t l1 = kb + (lane & 7) * 144;
#pragma unroll
  for (int k = 0; k < 8; k++) {
    h2 q0;
    ldsm1(l1 + k * 16, q0.r); ldsm1(l1 + 8 * 144 + k * 16, q0.i);
    const uint2 mu = lds64(kb + 2304 + (k * 4 + (lane & 3)) * 8);
    const h2 q1 = hmul(q0, h2{mu.x, mu.y}), q2 = hmul(q1, h2{mu.x, mu.y}), q3 = hmul(q2, h2{mu.x, mu.y});
#pragma unroll
    for (int nb = 0; nb < 3; nb++) mma16816(acc[nb], q0.r, q1.r, q0.i, q1.i, bf[nb][k][0], bf[nb][k][1]);
#pragma unroll
    for (int nb = 0; nb < 3; nb++) mma16816(acc[3 + nb], q2.r, q3.r, q2.i, q3.i, bf[nb][k][0], bf[nb][k][1]);
  }
  __syncwarp();
  const int g = lane >> 2, c = lane & 3;
  const uint32_t d0 = kb + lane * 4, d2 = kb + (512 + 68 * (g & 1) + (g >> 1) + (c < 2 ? 16 * c : 64)) * 2;
  const uint32_t d1 = kb + (c < 2 ? 256 + 4 * g + 2 * c : 256 + 64 * c + 2 * g) * 2, s1 = c < 2 ? 64 : 32;
#pragma unroll
  for (int q = 0; q < 4; q++) {
    const int mb = (q >> 1) * 3, o = (q & 1) * 2;
    sts32(d0 + q * 128, pack_h2(acc[mb][o], acc[mb][o + 1]));
    sts32(d1 + q * s1, pack_h2(acc[mb + 1][o], acc[mb + 1][o + 1]));
    const uint32_t v = pack_h2(acc[mb + 2][o], acc[mb + 2][o + 1]);
    if (c < (q == 0 ? 3 : 2)) sts16(d2 + q * 8, v);
    if (c < 2) sts16(d2 + q * 8 + 64, v >> 16);
  }
}

template <int I>
__device__ __forceinline__ void cv_load(uint32_t (&a)[RING][4], uint32_t ta, uint32_t zero) {
  const uint32_t t = ta + (I & 1) * 64 + ((I >> 1) & 1) * 256 + (I >> 2) * 1024;
  a[I % RING][0] = lds32(t); a[I % RING][2] = lds32(t - 32);
  if (I < 16) { a[I % RING][1] = lds32(t + 512); a[I % RING][3] = lds32(t + 480); }
  else {
    asm volatile("and.b32 %0, %1, %2;" : "=r"(a[I % RING][1]) : "r"(a[I % RING][0]), "r"(zero));
    asm volatile("and.b32 %0, %1, %2;" : "=r"(a[I % RING][3]) : "r"(a[I % RING][2]), "r"(zero));
  }
}
template <int N> __device__ __forceinline__ void cv_narrow(float (&acc)[64]) {
  wg_wait<0>();
#pragma unroll
  for (int i = 0; i < N / 2; i++) asm volatile("mov.b32 %0, %1;" : "=f"(acc[i]) : "f"(acc[i]));
}
template <int I>
__device__ __forceinline__ void cv_step(float (&acc)[64], uint32_t (&a)[RING][4], uint32_t ta, uint64_t db, uint32_t zero,
                                        unsigned* align, uint32_t nosig) {
  wg_fence();
  cv_rs<128 - 16 * (I >> 2)>(acc, a[I % RING], db + (I & 1) * 2 + ((I >> 1) & 1) * 8 + (I >> 2) * 32, I > 0);
  wg_commit();
  if constexpr (I == 0) { cv_load<2>(a, ta, zero); cv_load<3>(a, ta, zero); }
  if constexpr (I == 0 && RING == 8) { cv_load<4>(a, ta, zero); cv_load<5>(a, ta, zero); }
  if constexpr (I == 1) { cv_load<RING - 2>(a, ta, zero); cv_load<RING - 1>(a, ta, zero); }
  if constexpr (I >= 2 && I + RING - 2 < 18) { wg_wait<2>(); cv_load<I + RING - 2>(a, ta, zero); }
  if constexpr (I == ALIGN_STEP)
    asm volatile("{.reg .pred p; setp.eq.u32 p, %1, 0; @p red.relaxed.gpu.global.add.u32 [%0], 1;}" ::"l"(align), "r"(nosig) : "memory");
  if constexpr (I < 17) cv_step<I + 1>(acc, a, ta, db, zero, align, nosig);
}
__device__ __forceinline__ void conv_channel(uint32_t* sout, unsigned* align, int ch, int dglob, int warp, int lane, uint32_t zero) {
  const int g = lane >> 2, c = lane & 3, wq = warp & 3, w0 = wq & 1, hi = wq >> 1;
  const uint32_t tc = SM_T + ch * TCH;
  const uint32_t ta = tc + (32 + 8 * w0 + 32 * hi + g - 2 * c) * 4;
  float acc[64];
  uint32_t a[RING][4];
  cv_load<0>(a, ta, zero);
  cv_load<1>(a, ta, zero);
  cv_step<0>(acc, a, ta, mkdesc(SM_U + ch * UCH, 16, 256, 3), zero, align, (threadIdx.x & 127) | (5 >> ch & 1));
  {
    const uint64_t wa = mkdesc(SM_W + ch * WCH, W7_OFF, W_PS, 0), wt = mkdesc(tc + 1120 * 4, 1024, 128, 0);
    cv_ss64(acc, wa, wt);
    wg_fence();
    cv_ss32(acc, wa + 8, wt + 32);
  }
  wg_commit();
  const float inv = ldsf(tc + NTW * 4);
  const int bar = 8 + (warp >> 2), p = 63 - c + hi, wv = 2 * (p & 3) + w0;
  const uint32_t xa = (warp < 4 ? SB + 4 * G2_SLOT : SM_W + 5 * WCH + (warp & 4) * 2176) + w0 * 4352 + g * 544 + (c - hi + 1) * 8;
  const uint32_t oa = tc + (p >> 2) * 256 + ((wv ^ ((dglob >> 1) & 3) ^ (wv >> 2)) << 5) + g * 4;
  wg_wait<0>();
#pragma unroll
  for (int j = 0; j < 15; j++) { acc[4 * j] += acc[4 * j + 6]; acc[4 * j + 1] += acc[4 * j + 7]; }
  auto fin = [&](int j) {
    const float2 r = lds64f(xa + j * 32);
    sts32(oa - j * 256, pack_b2((acc[4 * j + 1] + r.y) * inv, (acc[4 * j] + r.x) * inv));
  };
  if (hi) {
#pragma unroll
    for (int j = 8; j < 16; j++) sts64f(xa + j * 32, acc[4 * j], acc[4 * j + 1]);
    if (c == 0) sts64(xa + 16 * 32, 0u, 0u);
    bar_sync(bar + 4, 128);
#pragma unroll
    for (int j = 0; j < 8; j++) fin(j);
  } else {
#pragma unroll
    for (int j = 0; j < 8; j++)
      if (j < 7 || c < 3) sts64f(xa + j * 32, acc[4 * j], acc[4 * j + 1]);
    bar_sync(bar + 4, 128);
#pragma unroll
    for (int j = 8; j < 16; j++) fin(j);
    if (c == 3) fin(7);
  }
  fence_async_smem();
  if (wq == 3) {
    bar_sync(bar, 128);
    if (lane == 0) { bulk_s2g(sout + dglob * 1024, tc, 4096); bulk_commit(); }
    __syncwarp();
  } else {
    bar_arrive(bar, 128);
  }
}

template <bool USE_SMID>
__global__ void __launch_bounds__(NTHREADS, 1)
s4_ffn_kernel(const Params P, const __grid_constant__ CUtensorMap tmXr, const __grid_constant__ CUtensorMap tmX,
              const __grid_constant__ CUtensorMap tmW1, const __grid_constant__ CUtensorMap tmW2,
              const __grid_constant__ CUtensorMap tmU, const __grid_constant__ CUtensorMap tmXe,
              const __grid_constant__ CUtensorMap tmO, const __grid_constant__ CUtensorMap tmS) {
  extern __shared__ uint8_t smem_raw[];
  const long long t_start = clock64();
  const int tid = threadIdx.x, lane = tid & 31;
  uint32_t vid = blockIdx.x;
  if (USE_SMID) asm("mov.u32 %0, %%smid;" : "=r"(vid));
  const int cta = vid < 120 ? vid : vid - 4;

  uint32_t p_are = 0, p_aim = 0, p_bre = 0, p_bim = 0, p_cre = 0, p_cim = 0, p_ldt = 0, p_dsk = 0;
  if (tid < 480) {
    const int po = cta * 960 + tid * 2, pc = cta * 5 + tid / 96;
    p_ldt = ldg16(P.logdt + pc);
    p_cre = ldg32(P.cre + po); p_cim = ldg32(P.cim + po); p_bre = ldg32(P.bre + po); p_bim = ldg32(P.bim + po);
    p_are = ldg32(P.are + po); p_aim = ldg32(P.aim + po);
    p_dsk = ldg16(P.dskip + pc);
  }
  const int warp = __shfl_sync(0xffffffffu, tid >> 5, 0);

  if (__builtin_expect(vid >= 120 && vid < 124, 0)) {
    unsigned old = 0;
    if (tid == 0) old = atomicAdd(&P.scr->cnt[C_CHK * 32], 1u);
    const int hid = vid - 120;
    if (tid == 0) {
      for (int i = 0; i < 8; i++) mbar_init(SM_BAR + i * 8, 1);
      asm volatile("fence.mbarrier_init.release.cluster;" ::: "memory");
    }
    if (tid < 32) sts32(SM_CS + tid * 4, 0x3F803F80u);
    fence_async_smem();
    __syncthreads();
    if (warp < 8) {
      const int wg = warp >> 2;
      auto load = [&](int k) {
        const uint32_t sl = wg * 4 + (k & 3);
        mbar_expect(SM_BAR + sl * 8, 24576);
        tma3d(SB + sl * 24576, &tmW1, 0, k * 64, (hid * 2 + wg) * 3, SM_BAR + sl * 8);
      };
      if ((tid & 127) == 0) {
        while (clock64() - t_start < T_H) {}
        for (int k = 0; k < 4; k++) load(k);
      }
      float acc[3][4];
#pragma unroll
      for (int i = 0; i < 12; i++) acc[i >> 2][i & 3] = 0.f;
#pragma unroll 1
      for (int k = 0; k < 10; k++) {
        const uint32_t sl = wg * 4 + (k & 3);
        mbar_wait(SM_BAR + sl * 8, (k >> 2) & 1);
        if (tid == 0 && (k & 1) == 0) TSX(7, 10 + (k >> 1));
        const uint64_t da = mkdesc(SB + sl * 24576, 8192, 1024, 1);
        wg_fence();
#pragma unroll
        for (int i = 0; i < 12; i++) wgmma_n8_ta(acc[i % 3], da + (i % 3) * 512 + (i / 3) * 128, mkdesc(SM_CS, 0, 128, 0));
        wg_commit();
        wg_wait<0>();
        bar_sync(1 + wg, 128);
        if ((tid & 127) == 0 && k < 6) load(k + 4);
      }
      if ((lane & 3) < 2) {
#pragma unroll
        for (int i = 0; i < 3; i++) {
          const float t = -((lane & 1) ? acc[i][2] : acc[i][0]), t0 = bf_round(t), t1 = bf_round(t - t0);
          P.scr->cs[hid * 384 + wg * 192 + i * 64 + (warp & 3) * 16 + (lane & 1) * 8 + (lane >> 2)] =
              make_uint4(pack_b2(t0, t1), pack_b2(t - t0 - t1, 0.f), 0u, 0u);
        }
      }
    }
    __syncthreads();
    if (tid == 0) {
      TSX(7, 8);
      red_release(&P.scr->cnt[(C_CS + hid) * 32]);
      TSX(7, 9);
      if (USE_SMID) poll_flag(&P.scr->cnt[C_CHK * 32], (old / 132 + 1) * 132);
    }
    return;
  }

  unsigned chk = 0;
  if (tid == 12 * 32) chk = atomicAdd(&P.scr->cnt[C_CHK * 32], 1u);
  int mt, ns;
  if (vid < 64) { mt = vid & 15; ns = vid >> 4; }
  else if (vid < 120) { const int t = vid - 64, q = t / 14; mt = 2 + t - q * 14; ns = 4 + q; }
  else { mt = vid & 1; ns = (vid - 116) >> 1; }

  if (warp == 15) {
    if (elect_one()) {
      mbar_init(B_XROW, 1);
      asm volatile("fence.mbarrier_init.release.cluster;" ::: "memory");
      mbar_expect(B_XROW, 16 * D_ * 2);
      while (clock64() - t_start < T_X) {}
      TSX(7, 0);
      tma5d(SM_U, &tmXr, cta * 4, B_XROW);
      tm_prefetch(&tmX); tm_prefetch(&tmW1); tm_prefetch(&tmW2);
      if ((uint32_t)__cvta_generic_to_shared(smem_raw) != SB) __trap();
#pragma unroll
      for (int i = 0; i < 34; i++)
        if (SM_BAR + i * 8 != B_XROW) mbar_init(SM_BAR + i * 8, (i < 19 && SM_BAR + i * 8 != B_CST) ? 1 : (i < 30 ? 2 : (i < 33 ? 8 : 7)));
      asm volatile("fence.mbarrier_init.release.cluster;" ::: "memory");
      TSX(7, 3);
    }
    __syncwarp();
    bar_arrive(9, 64);
    if (elect_one()) {
      mbar_expect(B_W2LD, 15360 + NTW * 4);
      while (clock64() - t_start < T_W2) {}
      TSX(7, 1);
#pragma unroll 1
      for (int u = 0; u < 3; u++) tma3d(SM_T + u * 5120, &tmW2, 0, (mt * 3 + u) * 32, ns * 5, B_W2LD);
      bulk_g2s(SM_T + 4 * TCH, P.idx, NTW * 4, B_W2LD);
      tm_prefetch(&tmU); tm_prefetch(&tmXe); tm_prefetch(&tmO); tm_prefetch(&tmS);
      while (clock64() - t_start < T_G1) {}
#pragma unroll 1
      for (int k = 0; k < 3; k++) {
        mbar_expect(B_FULL1 + 8 * k, G1_STAGE);
        tma2d(SB + k * G1_STAGE, &tmX, k * 64, mt * 128, B_FULL1 + 8 * k);
        tma3d(SB + k * G1_STAGE + 16384, &tmW1, 0, k * 64, ns * 3, B_FULL1 + 8 * k);
      }
      bulk_prefetch(P.w1 + 192 * F_ + (size_t)cta * 5376, 5376 * 2);
      TSX(7, 2);
    }
    __syncwarp();
    mbar_wait(B_XROW, 0);
    TS(1);
    {
      float sm[4], q0[4], q1[4], ac[6][4];
#pragma unroll
      for (int i = 0; i < 6; i++) ac[i][0] = ac[i][1] = ac[i][2] = ac[i][3] = 0.f;
      const uint32_t la = SM_U + (lane & 15) * 128 + (((lane >> 4) ^ (lane & 7)) << 4);
      uint32_t a[2][4][4];
      auto ld4 = [&](int h, uint32_t o) {
#pragma unroll
        for (int k = 0; k < 4; k++) ldsm4((la ^ (k << 5)) + o, a[h][k][0], a[h][k][1], a[h][k][2], a[h][k][3]);
      };
      auto mm4 = [&](int h) {
        uint32_t b[4][4];
#pragma unroll
        for (int k = 0; k < 16; k++) b[k >> 2][k & 3] = a[h][k >> 2][((k & 1) << 1) | ((k >> 1) & 1)] ^ P.zero;
#pragma unroll
        for (int k = 0; k < 4; k++) {
          mma16816b(ac[k & 1], a[h][k][0], a[h][k][1], a[h][k][2], a[h][k][3], 0x3F803F80u, 0x3F803F80u);
          mma16816b(ac[2 + (k & 1)], a[h][k][0], a[h][k][1], a[h][k][2], a[h][k][3], b[k][0], b[k][1]);
          mma16816b(ac[4 + (k & 1)], a[h][k][0], a[h][k][1], a[h][k][2], a[h][k][3], b[k][2], b[k][3]);
        }
      };
      ld4(0, 0);
#pragma unroll 1
      for (int i = 0; i < 5; i++) {
        ld4(1, i * 4096 + 2048);
        mm4(0);
        ld4(0, i * 4096 + 4096);
        mm4(1);
      }
#pragma unroll
      for (int i = 0; i < 4; i++) { sm[i] = ac[0][i] + ac[1][i]; q0[i] = ac[2][i] + ac[3][i]; q1[i] = ac[4][i] + ac[5][i]; }
      bar_arrive(2, 512);
      const int src = (lane & 7) * 4 + ((lane & 7) >> 1), odd = (lane >> 2) & 1;
      const float t0 = __shfl_sync(0xffffffffu, odd ? q0[1] : q0[0], src), t1 = __shfl_sync(0xffffffffu, odd ? q1[3] : q1[2], src);
      const float m0 = __shfl_sync(0xffffffffu, sm[0], src), m1 = __shfl_sync(0xffffffffu, sm[2], src);
      const float mean = ((lane & 8) ? m1 : m0) * (1.f / D_);
      float var = fmaf(-mean, mean, ((lane & 8) ? t1 : t0) * (1.f / D_));
      if (mean * mean > 32.f * var) {
        var = 0.f;
#pragma unroll 1
        for (int i = 0; i < D_ / 2; i++) {
          const uint32_t w = lds32(SM_U + (lane & 15) * 128 + (i >> 5) * 2048 + (i & 31) * 4);
          const float d0 = bf_lo(w) - mean, d1 = bf_hi(w) - mean;
          var = fmaf(d0, d0, fmaf(d1, d1, var));
        }
        var *= 1.f / D_;
      }
      const float mb = bf_round(mean);
      float sd;
      asm("sqrt.approx.ftz.f32 %0, %1;" : "=f"(sd) : "f"(bf_round(bf_round(var) + 1e-5f)));
      const float rs = __fdividef(1.f, bf_round(sd));
      if (lane < 16) {
        const int tok = (lane >> 3) * 2 + ((lane >> 1) & 3) * 4 + (lane & 1);
        P.scr->stats[cta * 16 + tok] = make_float2(0.5f * rs, mb);
        sts64f(SM_LNST + tok * 8, rs, -rs * mb);
      }
      __syncwarp();
    }
    TS(2);
    bar_arrive(4, 32 + (15 - LN_W0) * 32);
  } else {
    const float dt = bf_round(expf(bf_lo(p_ldt))), dsk = bf_lo(p_dsk);
    TS(0);
    kgen_warp(SM_W + warp * KBUF, lane, p_are, p_aim, p_bre, p_bim, p_cre, p_cim, dt, dsk);
    if (tid == 12 * 32) sts32(SM_EPOCH, chk / 132 + 1);
    TS(1);
    if (warp == 11) {
      bar_sync(9, 64);
      if (elect_one()) {
        mbar_wait(B_W2LD, 0);
        bulk_s2g(P.scr->w2r + (size_t)ns * 24 * 10240 + mt * 15360, SM_T, 15360);
        bulk_commit();
        TS1(4);
        bulk_wait0();
      }
      __syncwarp();
    }
    bar_sync(2, 512);
    if (warp >= LN_W0) {
      constexpr int NW = 15 - LN_W0;
      bar_sync(4, 32 + NW * 32);
      const uint32_t la = SM_U + (lane & 15) * 128 + (((lane >> 4) ^ (lane & 7)) << 4);
      uint2* uo = reinterpret_cast<uint2*>(P.scr->uT + (127 - cta) * (D_ * 32)) + lane;
      const uint4 sa = lds128(SM_LNST + (lane & 3) * 32), sb = lds128(SM_LNST + (lane & 3) * 32 + 16);
      auto nrm = [&](uint32_t v, const uint4& t) {
        return pack_h2(fmaf(bf_lo(v), __uint_as_float(t.x), __uint_as_float(t.y)), fmaf(bf_hi(v), __uint_as_float(t.z), __uint_as_float(t.w)));
      };
#pragma unroll 1
      for (int i = 14 - warp; i < 40; i += 3 * NW) {
        uint32_t r[3][4];
#pragma unroll
        for (int k = 0; k < 3; k++) {
          const int t = i + NW * k;
          ldsm4t((la ^ ((t & 3) << 5)) + (t >> 2) * 2048, r[k][0], r[k][1], r[k][2], r[k][3]);
        }
#pragma unroll
        for (int k = 0; k < 3; k++) {
          if (i + NW * k < 40) {
            uo[(i + NW * k) * 64] = make_uint2(nrm(r[k][0], sa), nrm(r[k][1], sb));
            uo[(i + NW * k) * 64 + 32] = make_uint2(nrm(r[k][2], sa), nrm(r[k][3], sb));
          }
        }
      }
      TS(2);
      if (warp < 8) bar_arrive(1, NW * 32); else bar_sync(1, NW * 32);
    }
  }
  const int g = lane >> 2, c = lane & 3;

  if (warp < 8) {
    float acc[96];
    {
      const uint64_t da0 = mkdesc(SB + (warp >> 2) * 8192, 16, 1024, 1), db0 = mkdesc(SB + 16384, 8192, 1024, 1);
      int s = 0, ps = 0;
      uint32_t ph = 0;
#pragma unroll 1
      for (int k = 0; k < 10; k++) {
        if (tid == 0) TSX(0, k);
        mbar_wait(B_FULL1 + 8 * s, ph);
        if (tid == 0) TSX(1, k);
        const uint64_t da = da0 + s * (G1_STAGE >> 4), db = db0 + s * (G1_STAGE >> 4);
        wg_fence();
        wgmma_n192(acc, da, db, k);
        wg_commit();
        wg_wait<1>();
        if ((tid & 127) == 0 && k > 0) mbar_arrive(B_EMPTY1 + 8 * ps);
#pragma unroll
        for (int kk = 1; kk < 4; kk++) wgmma_n192(acc, da + kk * 2, db + kk * 128, 1);
        wg_commit();
        ps = s;
        if (++s == 3) { s = 0; ph ^= 1; }
      }
    }
    mbar_wait(B_CST, 0);
    const float2 s0 = lds64f(SM_ST + (warp * 16 + g) * 8), s1 = lds64f(SM_ST + (warp * 16 + 8 + g) * 8);
    {
      const uint32_t sel = c == 0 ? 0x3232u : (c == 1 ? 0x4432u : 0x4444u);
      uint32_t am[4];
      asm volatile("prmt.b32 %0, %1, 0, %2;" : "=r"(am[0]) : "r"(__float_as_uint(s0.y)), "r"(sel));
      asm volatile("prmt.b32 %0, %1, 0, %2;" : "=r"(am[1]) : "r"(__float_as_uint(s1.y)), "r"(sel));
      asm volatile("and.b32 %0, %1, %2;" : "=r"(am[2]) : "r"(am[0]), "r"(P.zero));
      asm volatile("and.b32 %0, %1, %2;" : "=r"(am[3]) : "r"(am[1]), "r"(P.zero));
      wg_fence();
      wgmma_n192_rs(acc, am, mkdesc(SM_CS, 0, 128, 0));
      wg_commit();
      wg_wait<0>();
    }
    TS(3);
    bar_sync(5, 288);
    TS(4);
    const int rho = lane & 7;
    const uint32_t sa = SM_HST + ((warp >> 1) * 32 + (lane & 8) * 2 + (warp & 1) * 8 + rho) * 128 + (((lane >> 4) ^ rho) << 4);
#pragma unroll
    for (int k3 = 0; k3 < 3; k3++) {
#pragma unroll
      for (int jj = 0; jj < 8; jj += 2) {
        uint32_t r[4];
#pragma unroll
        for (int h = 0; h < 2; h++) {
          const int j = k3 * 8 + jj + h;
          const float h0 = acc[4 * j] * s0.x, h1 = acc[4 * j + 1] * s0.x, h2 = acc[4 * j + 2] * s1.x, h3 = acc[4 * j + 3] * s1.x;
          r[2 * h] = pack_b2(fmaf(h0, tanh_fast(h0), h0), fmaf(h1, tanh_fast(h1), h1));
          r[2 * h + 1] = pack_b2(fmaf(h2, tanh_fast(h2), h2), fmaf(h3, tanh_fast(h3), h3));
        }
        stsm4((sa ^ (jj << 4)) + k3 * G2_SLOT, r[0], r[1], r[2], r[3]);
      }
      fence_async_smem();
      __syncwarp();
      if (lane == 0) {
        mbar_arrive(B_HST + 8 * k3);
        if (k3 == 1 && warp == 4) { bulk_wait0(); red_release(&P.scr->cnt[(C_H + mt * 2) * 32]); }
        if (warp == (k3 ? 5 : 4)) {
          mbar_wait(B_HST + 8 * k3, 0);
          bulk_s2g(P.scr->h + (size_t)(mt * 24 + ns * 3 + k3) * 16384, SM_HST + k3 * G2_SLOT, 16384);
          bulk_commit();
          if (k3 == 2) { bulk_wait0(); red_release(&P.scr->cnt[(C_H + mt * 2 + 1) * 32]); }
        }
      }
      __syncwarp();
    }
    TS(5);
    if (warp == 6 && elect_one()) {
      poll_flag(&P.scr->cnt[(C_H + mt * 2) * 32], lds32(SM_EPOCH) * 8);
      fence_async();
      TS1(6);
      bulk_g2s(SB + 3 * G2_SLOT, P.scr->h + (size_t)(mt * 24 + (ns ? 0 : 3)) * 16384, 16384, B_FULL2 + 24);
    }
    __syncwarp();
  } else {
    const int at = tid - 256;
    const int tt = warp < 12 ? at : at - 32;
    if (warp == 15) {
      if (elect_one()) {
        {
          int s = 0;
          uint32_t ph = 0;
#pragma unroll 1
          for (int k = 3; k < 10; k++) {
            mbar_wait(B_EMPTY1 + 8 * s, ph);
            TSX(2, k);
            mbar_expect(B_FULL1 + 8 * s, G1_STAGE);
            tma2d(SB + s * G1_STAGE, &tmX, k * 64, mt * 128, B_FULL1 + 8 * s);
            tma3d(SB + s * G1_STAGE + 16384, &tmW1, 0, k * 64, ns * 3, B_FULL1 + 8 * s);
            if (++s == 3) { s = 0; ph ^= 1; }
          }
        }
        TS1(0);
        poll_flag(&P.scr->cnt[(C_CS + (ns >> 1)) * 32], lds32(SM_EPOCH));
        fence_async();
        mbar_expect(B_CST, 3072);
        bulk_g2s(SM_CS, P.scr->cs + ns * 192, 3072, B_CST);
        TS1(13);
      }
      __syncwarp();
      bar_sync(5, 288);
      if (elect_one()) {
        mbar_wait(B_CST, 0);
        fence_async();
#pragma unroll 1
        for (int q = 0; q < 4; q++) {
          mbar_expect(B_FULL2 + 8 * q, q < 3 ? 10240 : G2_SLOT);
          bulk_g2s(SB + q * G2_SLOT + 16384, P.scr->w2r + (size_t)(ns * 24 + (q < 3 ? ns * 3 + q : (ns ? 0 : 3))) * 10240, 10240,
                   B_FULL2 + 8 * q);
        }
      }
      __syncwarp();
    } else {
    if (warp == 12) {
      if (elect_one()) {
        red_release(&P.scr->cnt[C_U * 32]);
        const unsigned ep = lds32(SM_EPOCH);
        TS1(4);
        poll_flag(&P.scr->cnt[C_U * 32], ep * 128);
        fence_async();
        TS1(13);
        mbar_expect(B_CST, 1024);
        bulk_g2s(SM_ST, P.scr->stats + mt * 128, 1024, B_CST);
        mbar_expect(B_ULD, 5 * UCH);
        tma3d(SM_U, &tmU, 0, 0, cta * 5, B_ULD);
      }
      __syncwarp();
    } else {
#pragma unroll 1
      for (int it = tt >> 5; it < 15; it += 6) {
        const int ch = it / 3, oc = min((it - ch * 3) * 31 + lane - 1, 81);
        const uint32_t k0 = SM_W + ch * 3 * KBUF;
        const uint4 a = lds128(k0 + oc * 16), b = lds128(k0 + KBUF + oc * 16), d = lds128(k0 + 2 * KBUF + oc * 16);
        const uint4 m0 = lds128(k0 + 2608);
        const int e0 = m0.x, e1 = lds32(k0 + KBUF + 2608), e2 = lds32(k0 + 2 * KBUF + 2608);
        const int em = min(max(max(max(e0, e1), e2) + 2, (int)((m0.z >> 23) & 255) - 6), 254);
        auto ratio = [&](int e) { const float r = __uint_as_float(max(127 + e - em, 0) << 23); return pack_h2(r, r); };
        const uint32_t r0 = ratio(e0), r1 = ratio(e1), r2 = ratio(e2);
        uint32_t x0 = hfma2(a.x, r0, hfma2(b.x, r1, hmul2(d.x, r2)));
        const uint32_t x1 = hfma2(a.y, r0, hfma2(b.y, r1, hmul2(d.y, r2)));
        const uint32_t x2 = hfma2(a.z, r0, hfma2(b.z, r1, hmul2(d.z, r2)));
        const uint32_t x3 = hfma2(a.w, r0, hfma2(b.w, r1, hmul2(d.w, r2)));
        if (oc == 0) x0 = hadd2(x0, pack_h2(__uint_as_float(m0.z) * __uint_as_float((261 - em) << 23), 0.f));
        const uint32_t xp = __shfl_up_sync(0xffffffffu, oc < 0 ? 0u : x3, 1);
        const uint32_t o = SM_T + ch * TCH + (oc < 32 ? 32 : CP_W - 256) * 4 + oc * 32;
        if (lane > 0) {
          sts128(o, __byte_perm(x0, xp, 0x7610), __byte_perm(x0, 0, 0x1032), __byte_perm(x1, x0, 0x7610), __byte_perm(x1, 0, 0x1032));
          sts128(o + 16, __byte_perm(x2, x1, 0x7610), __byte_perm(x2, 0, 0x1032), __byte_perm(x3, x2, 0x7610), __byte_perm(x3, 0, 0x1032));
        }
        if (oc < 0) sts32(SM_T + ch * TCH + NTW * 4, __float_as_uint(__uint_as_float((em - 7) << 23) * __uint_as_float(m0.y)));
      }
      TS(3);
      bar_sync(7, 192);
#pragma unroll 1
      for (int e = tt; e < (int)NTW - 256; e += 192) {
        const uint32_t wo = SM_T + (e < 32 ? e : e + 256) * 4;
        const uint32_t ix = lds32(wo + 4 * TCH), src = SM_T + (ix & 0xffffu), sel = ix >> 16;
#pragma unroll
        for (int ch = 0; ch < 5; ch++) sts32(wo + ch * TCH, __byte_perm(lds32(src + ch * TCH), 0u, sel));
      }
    }
    TS(5);
    bar_sync(3, 224);
    mbar_wait(B_ULD, 0);
    TS(6);
    {
      auto uaddr = [&](int e) { return SM_U + ((e ^ 1 ^ ((e >> 3) & 1)) << 4); };
      auto waddr = [&](int e) {
        return SM_W + ((e & 4) + (e & 1) * 2 + ((e >> 4) & 1)) * W_PS + ((e >> 5) * 4 + ((e >> 2) & 2) + ((e >> 1) & 1)) * 16;
      };
      const uint32_t ua0 = uaddr(257 - lane) + 8, ub0 = uaddr(256 - lane), uc0 = uaddr(255 - lane);
      const uint32_t o90 = waddr(lane + 1), o70 = waddr(lane) + W7_OFF;
#pragma unroll 1
      for (int it = warp - 8; it < 20; it += 7) {
        const int ch = it >> 2, q = it & 3;
        const bool wrap = q == 3 && lane == 31;
        const uint32_t ua = ua0 - q * 512, ub = ub0 - q * 512, uc = uc0 - q * 512;
        const uint32_t o9 = o90 + (wrap ? -64 : q * 64), o7 = o70 + q * 64, m9 = wrap ? 0u : 0xffffffffu;
        const uint2 pa = lds64(ua + ch * UCH), pc = lds64(uc + ch * UCH);
        const uint4 pb = lds128(ub + ch * UCH);
        const uint32_t E[8] = {pa.x, pa.y, pb.x, pb.y, pb.z, pb.w, pc.x, pc.y};
        uint32_t O[7], oo[6], w7[4], w9[4];
#pragma unroll
        for (int i = 0; i < 7; i++) O[i] = __byte_perm(E[i], E[i + 1], 0x5432);
#pragma unroll
        for (int i = 0; i < 6; i++) oo[i] = hadd2(O[i], E[i + 1]);
#pragma unroll
        for (int i = 0; i < 4; i++) {
          w7[i] = hadd2(hadd2(oo[i], oo[i + 1]), hadd2(oo[i + 2], O[i + 3]));
          w9[i] = hadd2(w7[i], hadd2(E[i], E[i + 4])) & m9;
        }
        sts128(o9 + ch * WCH, w9[0], w9[1], w9[2], w9[3]);
        sts128(o7 + ch * WCH, w7[0], w7[1], w7[2], w7[3]);
      }
    }
    fence_async_smem();
    __syncwarp();
    if (lane == 0) mbar_arrive(B_PREP);
    TS(7);
    }
  }

  TS(8);
  if (warp < 4 || warp >= 8) {
    const int c0 = warp < 4 ? 4 : (warp >> 1) & 2, c1 = min(c0 + 2, 5);
    mbar_wait(B_ULD, 0);
    mbar_wait(B_PREP, 0);
    if (warp >= 12) mbar_wait(B_HST + STAG_K * 8, 0);
#pragma unroll 1
    for (int ch = c0; ch < c1; ch++) {
      conv_channel(P.scr->s, &P.scr->cnt[(C_AL + (mt >> 1)) * 32], ch, cta * 5 + ch, warp, lane, P.zero);
      TS(10 + (ch & 1));
    }
    bulk_wait0();
  } else if (warp == 7) {
    if (lane == 0) poll_flag(&P.scr->cnt[(C_AL + (mt >> 1)) * 32], lds32(SM_EPOCH) * 48);
    __syncwarp();
  }
  TS(9);
  bar_sync(6, 512);
  if (warp >= 8) {
    if (elect_one()) {
      if (warp == 15) {
        const uint8_t* hp = P.scr->h + (size_t)mt * 24 * 16384;
        const uint8_t* wp = P.scr->w2r + (size_t)ns * 24 * 10240;
        int q = 4;
#pragma unroll 1
        for (int kbl = 0; kbl < 3; kbl++) {
          if (kbl == 1) mbar_wait(B_H12, 0);
          fence_async();
          TS1(4 + kbl);
#pragma unroll 1
          for (int r = kbl ? 0 : 1; r < 7; r++, q++) {
            const int s = q & 7, kb = 3 * (r + (r >= ns)) + kbl;
            mbar_wait(B_EMPTY2 + 8 * s, ((q >> 3) & 1) ^ 1);
            mbar_expect(B_FULL2 + 8 * s, G2_SLOT);
            bulk_g2s(SB + s * G2_SLOT, hp + kb * 16384, 16384, B_FULL2 + 8 * s);
            bulk_g2s(SB + s * G2_SLOT + 16384, wp + kb * 10240, 10240, B_FULL2 + 8 * s);
          }
        }
        mbar_expect(B_XS, 40960);
        mbar_wait(B_EMPTY2, 0);
        tma2d(SM_XT, &tmXe, ns * 80, mt * 128, B_XS);
        mbar_wait(B_SOK, 0);
        fence_async();
        mbar_wait(B_EMPTY2 + 8, 0);
        tma2d(SM_S, &tmS, mt * 128, ns * 80, B_XS);
        TS1(12);
      } else if (warp == 14) {
        red_release(&P.scr->cnt[(C_S + (cta >> 4)) * 32]);
      } else if (warp >= 12) {
        const bool h = warp == 12;
        poll_flag(&P.scr->cnt[(h ? C_H + mt * 2 + 1 : C_S + ns) * 32], lds32(SM_EPOCH) * (h ? 8 : 16));
        mbar_arrive(h ? B_H12 : B_SOK);
        TS1(12);
      }
    }
    return;
  }
  TS(10);

  {
    float acc[40];
    const uint64_t da0 = mkdesc(SB + (warp >> 2) * 8192, 16, 1024, 1), db0 = mkdesc(SB + 16384, 1024, 256, 3);
#pragma unroll 1
    for (int q = 0; q < 24; q++) {
      const int s = q & 7;
      mbar_wait(B_FULL2 + 8 * s, (q >> 3) & 1);
      if (tid == 0 && (q & 3) == 0) TSX(3, q >> 2);
      const uint64_t da = da0 + s * (G2_SLOT >> 4), db = db0 + s * (G2_SLOT >> 4);
      wg_fence();
#pragma unroll
      for (int kk = 0; kk < 4; kk++) wgmma_n80(acc, da + kk * 2, db + (kk >> 1) * 320 + (kk & 1) * 32, kk ? 1 : q);
      wg_commit();
      wg_wait<1>();
      if ((tid & 127) == 0 && q > 0) mbar_arrive(B_EMPTY2 + 8 * ((s + 7) & 7));
    }
    wg_wait<0>();
    TS(11);
    mbar_wait(B_XS, 0);
    TS(12);
    const int r0 = (warp >> 1) * 32 + (warp & 1) * 8;
    const uint32_t xa = SM_XT + (r0 + (lane & 8) * 2 + (lane & 7)) * 160 + ((((lane >> 4) ^ (lane >> 2)) & 1) << 4);
    const uint32_t sa = SM_S + c * 512 + ((warp ^ c ^ (warp >> 2)) << 5) + g * 4;
    const bool sw = g >= 4;
#pragma unroll
    for (int jj = 0; jj < 10; jj += 2) {
      uint32_t x0, x1, x2, x3, p[4];
      ldsm4(xa + jj * 16, x0, x1, x2, x3);
#pragma unroll
      for (int h = 0; h < 2; h++) {
        const int j = jj + h;
        const uint32_t w0 = lds32(sa + j * 2048), w1 = lds32(sa + j * 2048 + 256);
        const float h0 = 0.5f * acc[4 * j], h1 = 0.5f * acc[4 * j + 1], h2 = 0.5f * acc[4 * j + 2], h3 = 0.5f * acc[4 * j + 3];
        p[2 * h] = pack_b2(fmaf(h0, tanh_fast(h0), h0) * bf_lo(w0), fmaf(h1, tanh_fast(h1), h1) * bf_lo(w1));
        p[2 * h + 1] = pack_b2(fmaf(h2, tanh_fast(h2), h2) * bf_hi(w0), fmaf(h3, tanh_fast(h3), h3) * bf_hi(w1));
      }
      stsm4(xa + jj * 16, badd2(x0, sw ? p[2] : p[0]), badd2(x1, sw ? p[3] : p[1]), badd2(x2, sw ? p[0] : p[2]),
            badd2(x3, sw ? p[1] : p[3]));
    }
    fence_async_smem();
    __syncwarp();
    if (elect_one()) {
      tma2d_store(&tmO, SM_XT + r0 * 160, ns * 80, mt * 128 + r0);
      tma2d_store(&tmO, SM_XT + r0 * 160 + 2560, ns * 80, mt * 128 + r0 + 16);
      bulk_commit();
      TS1(13);
      bulk_wait0_read();
      TS1(14);
    }
  }
}

typedef CUresult (*EncodeFn)(CUtensorMap*, CUtensorMapDataType, cuuint32_t, void*, const cuuint64_t*, const cuuint64_t*,
                             const cuuint32_t*, const cuuint32_t*, CUtensorMapInterleave, CUtensorMapSwizzle,
                             CUtensorMapL2promotion, CUtensorMapFloatOOBfill);

void make_map(EncodeFn enc, CUtensorMap* m, void* base, int rank, const cuuint64_t* dims, const cuuint64_t* strides,
              const cuuint32_t* box, CUtensorMapSwizzle sw) {
  const cuuint32_t es[5] = {1, 1, 1, 1, 1};
  enc(m, CU_TENSOR_MAP_DATA_TYPE_BFLOAT16, rank, base, dims, strides, box, es, CU_TENSOR_MAP_INTERLEAVE_NONE, sw,
      CU_TENSOR_MAP_L2_PROMOTION_L2_128B, CU_TENSOR_MAP_FLOAT_OOB_FILL_NONE);
}

}

extern "C" void kernel_launch(void* const* d_in, const int* in_sizes, int n_in, void* d_out, int out_size) {
  (void)in_sizes; (void)n_in; (void)out_size;
  static EncodeFn enc = nullptr;
  static int nsm = 0;
  static void *p_scr = nullptr, *p_idx = nullptr;
  if (!enc) {
    void* fn = nullptr;
    cudaDriverEntryPointQueryResult q;
    cudaGetDriverEntryPoint("cuTensorMapEncodeTiled", &fn, cudaEnableDefault, &q);
    enc = (EncodeFn)fn;
    int dev = 0;
    cudaGetDevice(&dev);
    cudaDeviceGetAttribute(&nsm, cudaDevAttrMultiProcessorCount, dev);
    cudaGetSymbolAddress(&p_scr, g_scr);
    cudaGetSymbolAddress(&p_idx, g_idx);
    cudaFuncSetAttribute(s4_ffn_kernel<true>, cudaFuncAttributeMaxDynamicSharedMemorySize, SMEM_BYTES);
    cudaFuncSetAttribute(s4_ffn_kernel<false>, cudaFuncAttributeMaxDynamicSharedMemorySize, SMEM_BYTES);
  }
  void* x = d_in[0];
  void* w1 = d_in[10];
  void* w2 = d_in[11];
  CUtensorMap tmX, tmW1, tmW2, tmU, tmXe, tmO, tmS, tmXr;
  {
    const cuuint64_t d[2] = {D_, L_}, s[1] = {D_ * 2};
    const cuuint32_t b0[2] = {64, 128}, b1[2] = {80, 128}, b2[2] = {80, 8};
    make_map(enc, &tmX, x, 2, d, s, b0, CU_TENSOR_MAP_SWIZZLE_128B);
    make_map(enc, &tmXe, x, 2, d, s, b1, CU_TENSOR_MAP_SWIZZLE_NONE);
    make_map(enc, &tmO, d_out, 2, d, s, b2, CU_TENSOR_MAP_SWIZZLE_NONE);
  }
  {
    const cuuint64_t d[3] = {64, D_, F_ / 64}, s[2] = {F_ * 2, 128};
    const cuuint32_t b[3] = {64, 64, 3};
    make_map(enc, &tmW1, w1, 3, d, s, b, CU_TENSOR_MAP_SWIZZLE_128B);
  }
  {
    const cuuint64_t d[3] = {16, F_, D_ / 16}, s[2] = {D_ * 2, 32};
    const cuuint32_t b[3] = {16, 32, 5};
    make_map(enc, &tmW2, w2, 3, d, s, b, CU_TENSOR_MAP_SWIZZLE_32B);
  }
  {
    const cuuint64_t d[3] = {16, 128, D_}, s[2] = {D_ * 32, 32};
    const cuuint32_t b[3] = {16, 136, 5};
    make_map(enc, &tmU, ((Scratch*)p_scr)->uT, 3, d, s, b, CU_TENSOR_MAP_SWIZZLE_32B);
  }
  {
    const cuuint64_t d[2] = {L_, D_}, s[1] = {L_ * 2};
    const cuuint32_t b[2] = {128, 80};
    make_map(enc, &tmS, ((Scratch*)p_scr)->s, 2, d, s, b, CU_TENSOR_MAP_SWIZZLE_NONE);
  }
  {
    const cuuint64_t d[5] = {64, 2, L_ / 4, 2, 10}, s[4] = {D_ * 2, D_ * 8, D_ * 4, 128};
    const cuuint32_t b[5] = {64, 2, 4, 2, 10};
    make_map(enc, &tmXr, x, 5, d, s, b, CU_TENSOR_MAP_SWIZZLE_128B);
  }
  Params P;
  P.are = (const __nv_bfloat16*)d_in[1]; P.aim = (const __nv_bfloat16*)d_in[2];
  P.bre = (const __nv_bfloat16*)d_in[3]; P.bim = (const __nv_bfloat16*)d_in[4];
  P.cre = (const __nv_bfloat16*)d_in[5]; P.cim = (const __nv_bfloat16*)d_in[6];
  P.logdt = (const __nv_bfloat16*)d_in[7]; P.dskip = (const __nv_bfloat16*)d_in[8];
  P.w1 = (const __nv_bfloat16*)d_in[10];
  P.zero = 0;
  P.scr = (Scratch*)p_scr;
  P.idx = (const uint32_t*)p_idx;
  if (nsm == 132) s4_ffn_kernel<true><<<132, NTHREADS, SMEM_BYTES>>>(P, tmXr, tmX, tmW1, tmW2, tmU, tmXe, tmO, tmS);
  else s4_ffn_kernel<false><<<132, NTHREADS, SMEM_BYTES>>>(P, tmXr, tmX, tmW1, tmW2, tmU, tmXe, tmO, tmS);
}
```

```cpp
#define KNOB 0
#include <cuda_runtime.h>
#include <cuda_bf16.h>
#include <cuda_fp16.h>
#include <cuda.h>
#include <stdint.h>

namespace {

constexpr int L_ = 2048, D_ = 640, F_ = 1536;
constexpr int NTHREADS = 512;
#define E2F 4
#define AUGK 1
#define TP 400
#define TX 900
#define TXD 400
#define TW1 2600
#define TG1 2900
constexpr int T_P0 = 250, T_PD = TP, T_X = TX, T_XD = TXD, T_W1 = TW1, T_G1 = TG1;

constexpr uint32_t SB = 1024;
constexpr uint32_t G1_STAGE = 20480;
constexpr uint32_t G2_SLOT = 26624;
constexpr uint32_t Y_ = SB + 6 * G1_STAGE;
constexpr uint32_t CB = 20480, SM_C = Y_ + 2048;
constexpr uint32_t SM_U = SM_C, UCH = 4352;
constexpr uint32_t SM_W = SM_C + 4352;
constexpr uint32_t W7_OFF = 2176, W_PS = 272, KBUF = 2624;
constexpr uint32_t SM_O = SM_C + 8704;
constexpr uint32_t SM_CP = SM_C + 12288;
constexpr uint32_t SM_T = SM_C + 13824;
constexpr uint32_t NTW = 1632;
constexpr uint32_t SM_CS = SM_C + 5 * CB;
constexpr uint32_t SM_ST = SM_CS + 3072;
constexpr uint32_t SM_BAR = SM_ST + 1024;
constexpr uint32_t SMEM_BYTES = SM_BAR + 512 - SB;
static_assert(SMEM_BYTES <= 232448, "smem");
static_assert(SM_W + 3 * KBUF <= SM_CP && (SM_T % 256) == 0 && (SM_U % 1024) == 0 && SB + 7 * G2_SLOT <= SM_C + 3 * CB, "smem alias");
static_assert(SB + 8 * G2_SLOT <= SM_CS, "ring");
constexpr uint32_t B_XROW = SM_BAR, B_FULL1 = SM_BAR + 8, B_FULL2 = SM_BAR + 56, B_ULD = SM_BAR + 120;
constexpr uint32_t B_W2LD = SM_BAR + 160, B_G1L = SM_BAR + 168, B_SOK = SM_BAR + 176, B_XS = SM_BAR + 184;
constexpr uint32_t B_W2RD = SM_BAR + 192, B_FREE = SM_BAR + 200;
constexpr uint32_t B_EMPTY1 = SM_BAR + 208, B_EMPTY2 = SM_BAR + 256, B_CST = SM_BAR + 320, B_PREP = SM_BAR + 328;
constexpr uint32_t B_HST = SM_BAR + 368, B_CVD = SM_BAR + 384, B_TAB = SM_BAR + 392;
constexpr uint32_t SM_EPOCH = SM_BAR + 408, SM_LNST = Y_;
constexpr uint32_t SM_HST = SB;
constexpr uint32_t SM_XT = SB;
constexpr uint32_t SM_S = SB + G2_SLOT;

struct Scratch {
  uint8_t h[16 * 24 * 16384];
  uint8_t uT[D_ * 128 * 32];
  uint8_t w2r[8 * 24 * 10240];
  uint32_t s[D_ * 16 * 64];
  unsigned long long stats[L_];
  unsigned long long cs[F_];
  unsigned cnt[32 * 32];
};
__device__ __align__(1024) Scratch g_scr;
constexpr int C_CHK = 0, C_U = 1, C_S = 8, C_H = 16, C_W2 = 24;

struct IdxTab { uint32_t v[NTW]; };
constexpr int kpos(int v) {
  if (v < 256) return v;
  if (v < 512) return 128 + (v >> 1);
  if (v < 1024) return 256 + (v >> 2);
  return 512 + 68 * ((v >> 3) & 1) + ((v - 1024) >> 4);
}
constexpr int bf16_lag(int l) {
  const int sh = l < 256 ? 0 : (l < 512 ? 1 : (l < 1024 ? 2 : 3));
  if (sh == 0) return l;
  const int q = l >> sh, r = l & ((1 << sh) - 1), half = 1 << (sh - 1);
  return (q + ((r > half || (r == half && (q & 1))) ? 1 : 0)) << sh;
}
constexpr int tap_src(int w, int hi) {
  if (w < 1120) {
    const int l = w - 32 - hi;
    return (l < 0 || l > 1028) ? -1 : kpos(bf16_lag(l));
  }
  const int r = w - 1120, n = 63 - ((r & 255) >> 2);
  const int lag = 1024 + 16 * n - 256 * ((r >> 1) & 1) - 64 * (r & 1) - 16 * hi + ((r >> 8) ? 8 : 16);
  return lag < 1032 ? -1 : kpos(lag);
}
constexpr IdxTab make_idx() {
  IdxTab t{};
  for (int w = 0; w < (int)NTW; w++) {
    const int lo = tap_src(w, 0), hi = tap_src(w, 1);
    const int p = lo >= 0 ? lo : (hi >= 0 ? hi : 256);
    const uint32_t sel = (lo >= 0 ? 0x10u : 0x44u) | (hi < 0 ? 0x4400u : (hi == p ? 0x1000u : 0x3200u));
    t.v[w] = (uint32_t)((p < 256 ? 0 : p - 256) * 4) | (sel << 16);
  }
  return t;
}
__device__ __align__(128) const IdxTab g_idx = make_idx();

struct Params {
  const __nv_bfloat16 *logdt, *are, *aim, *bre, *bim, *cre, *cim, *dskip, *w1, *w2;
  Scratch* scr;
  const uint32_t* idx;
  uint32_t zero;
};

__device__ __forceinline__ bool elect_one() {
  uint32_t p;
  asm volatile("{.reg .pred P; elect.sync _|P, 0xffffffff; selp.u32 %0,1,0,P;}" : "=r"(p));
  return p;
}
__device__ __forceinline__ void mbar_init(uint32_t a, uint32_t c) {
  asm volatile("mbarrier.init.shared::cta.b64 [%0], %1;" ::"r"(a), "r"(c) : "memory");
}
__device__ __forceinline__ void mbar_expect(uint32_t a, uint32_t b) {
  asm volatile("mbarrier.arrive.expect_tx.shared::cta.b64 _, [%0], %1;" ::"r"(a), "r"(b) : "memory");
}
__device__ __forceinline__ void mbar_arrive(uint32_t a) {
  asm volatile("mbarrier.arrive.shared::cta.b64 _, [%0];" ::"r"(a) : "memory");
}
__device__ __forceinline__ void mbar_wait(uint32_t a, uint32_t ph) {
  asm volatile(
      "{.reg .pred p; .reg .u32 n; mov.u32 n, 0;\n"
      "LW%=: mbarrier.try_wait.parity.shared::cta.b64 p, [%0], %1;\n"
      "@p bra LD%=; add.u32 n, n, 1; setp.lt.u32 p, n, 20000; @p bra LW%=;\n"
      "LD%=: }" ::"r"(a), "r"(ph) : "memory");
}
__device__ __forceinline__ void bar_sync(int id, int n) { asm volatile("bar.sync %0, %1;" ::"r"(id), "r"(n) : "memory"); }
__device__ __forceinline__ void bar_arrive(int id, int n) { asm volatile("bar.arrive %0, %1;" ::"r"(id), "r"(n) : "memory"); }
__device__ __forceinline__ void fence_async() { asm volatile("fence.proxy.async.global;" ::: "memory"); }
__device__ __forceinline__ void fence_async_smem() { asm volatile("fence.proxy.async.shared::cta;" ::: "memory"); }
__device__ __forceinline__ void red_release(unsigned* p) {
  asm volatile("red.release.gpu.global.add.u32 [%0], 1;" ::"l"(p) : "memory");
}
__device__ __forceinline__ void poll_flag(const unsigned* p, unsigned target) {
  for (int n = 0; n < 20000; n++) {
    unsigned v;
    asm volatile("ld.acquire.gpu.global.u32 %0, [%1];" : "=r"(v) : "l"(p) : "memory");
    if ((int)(v - target) >= 0) break;
  }
}
__device__ __forceinline__ void st_tagged(unsigned long long* p, uint32_t lo, uint32_t hi_half, uint32_t tag) {
  const unsigned long long v = lo | ((unsigned long long)((hi_half & 0xffff0000u) | (tag & 0xffffu)) << 32);
  asm volatile("st.relaxed.gpu.global.u64 [%0], %1;" ::"l"(p), "l"(v) : "memory");
}
__device__ __forceinline__ unsigned long long ld_relaxed(const unsigned long long* p) {
  unsigned long long v;
  asm volatile("ld.relaxed.gpu.global.u64 %0, [%1];" : "=l"(v) : "l"(p) : "memory");
  return v;
}
__device__ __forceinline__ void bulk_g2s(uint32_t dst, const void* src, uint32_t bytes, uint32_t bar) {
  asm volatile("cp.async.bulk.shared::cluster.global.mbarrier::complete_tx::bytes [%0], [%1], %2, [%3];" ::"r"(dst),
               "l"(src), "r"(bytes), "r"(bar) : "memory");
}
__device__ __forceinline__ void bulk_s2g(void* dst, uint32_t src, uint32_t bytes) {
  asm volatile("cp.async.bulk.global.shared::cta.bulk_group [%0], [%1], %2;" ::"l"(dst), "r"(src), "r"(bytes) : "memory");
}
__device__ __forceinline__ void bulk_prefetch(const void* src, uint32_t bytes) {
  asm volatile("cp.async.bulk.prefetch.L2.global [%0], %1;" ::"l"(src), "r"(bytes) : "memory");
}
__device__ __forceinline__ void bulk_commit() { asm volatile("cp.async.bulk.commit_group;" ::: "memory"); }
__device__ __forceinline__ void bulk_wait0() { asm volatile("cp.async.bulk.wait_group 0;" ::: "memory"); }
__device__ __forceinline__ void bulk_wait0_read() { asm volatile("cp.async.bulk.wait_group.read 0;" ::: "memory"); }
__device__ __forceinline__ void tma2d(uint32_t dst, const CUtensorMap* m, int c0, int c1, uint32_t bar) {
  asm volatile("cp.async.bulk.tensor.2d.shared::cluster.global.mbarrier::complete_tx::bytes [%0], [%1, {%3, %4}], [%2];"
               ::"r"(dst), "l"(m), "r"(bar), "r"(c0), "r"(c1) : "memory");
}
__device__ __forceinline__ void tma3d(uint32_t dst, const CUtensorMap* m, int c0, int c1, int c2, uint32_t bar) {
  asm volatile("cp.async.bulk.tensor.3d.shared::cluster.global.mbarrier::complete_tx::bytes [%0], [%1, {%3, %4, %5}], [%2];"
               ::"r"(dst), "l"(m), "r"(bar), "r"(c0), "r"(c1), "r"(c2) : "memory");
}
__device__ __forceinline__ void tma5d(uint32_t dst, const CUtensorMap* m, int c2, int c4, uint32_t bar) {
  asm volatile("cp.async.bulk.tensor.5d.shared::cluster.global.mbarrier::complete_tx::bytes [%0], [%1, {0, 0, %3, 0, %4}], [%2];"
               ::"r"(dst), "l"(m), "r"(bar), "r"(c2), "r"(c4) : "memory");
}
__device__ __forceinline__ void tma2d_store(const CUtensorMap* m, uint32_t src, int c0, int c1) {
  asm volatile("cp.async.bulk.tensor.2d.global.shared::cta.bulk_group [%0, {%2, %3}], [%1];" ::"l"(m), "r"(src), "r"(c0),
               "r"(c1) : "memory");
}
__device__ __forceinline__ void tm_prefetch(const CUtensorMap* m) {
  asm volatile("prefetch.tensormap [%0];" ::"l"(m) : "memory");
}
__device__ __forceinline__ uint64_t mkdesc(uint32_t addr, uint32_t lbo, uint32_t sbo, uint32_t mode) {
  return (uint64_t)((addr & 0x3FFFF) >> 4) | ((uint64_t)(lbo >> 4) << 16) | ((uint64_t)(sbo >> 4) << 32) |
         ((uint64_t)mode << 62);
}
__device__ __forceinline__ void wg_fence() { asm volatile("wgmma.fence.sync.aligned;" ::: "memory"); }
__device__ __forceinline__ void wg_commit() { asm volatile("wgmma.commit_group.sync.aligned;" ::: "memory"); }
template <int N> __device__ __forceinline__ void wg_wait() {
  asm volatile("wgmma.wait_group.sync.aligned %0;" ::"n"(N) : "memory");
}
__device__ __forceinline__ void wgmma_n192(float (&d)[96], uint64_t da, uint64_t db, int acc) {
  asm volatile(
      "{.reg .pred p; setp.ne.b32 p, %98, 0;\n"
      "wgmma.mma_async.sync.aligned.m64n192k16.f32.bf16.bf16 {"
      "%0,%1,%2,%3,%4,%5,%6,%7,%8,%9,%10,%11,%12,%13,%14,%15,"
      "%16,%17,%18,%19,%20,%21,%22,%23,%24,%25,%26,%27,%28,%29,%30,%31,"
      "%32,%33,%34,%35,%36,%37,%38,%39,%40,%41,%42,%43,%44,%45,%46,%47,"
      "%48,%49,%50,%51,%52,%53,%54,%55,%56,%57,%58,%59,%60,%61,%62,%63,"
      "%64,%65,%66,%67,%68,%69,%70,%71,%72,%73,%74,%75,%76,%77,%78,%79,"
      "%80,%81,%82,%83,%84,%85,%86,%87,%88,%89,%90,%91,%92,%93,%94,%95"
      "}, %96, %97, p, 1, 1, 0, 1;}\n"
      :
        "+f"(d[0]), "+f"(d[1]), "+f"(d[2]), "+f"(d[3]), "+f"(d[4]), "+f"(d[5]), "+f"(d[6]), "+f"(d[7]),
        "+f"(d[8]), "+f"(d[9]), "+f"(d[10]), "+f"(d[11]), "+f"(d[12]), "+f"(d[13]), "+f"(d[14]), "+f"(d[15]),
        "+f"(d[16]), "+f"(d[17]), "+f"(d[18]), "+f"(d[19]), "+f"(d[20]), "+f"(d[21]), "+f"(d[22]), "+f"(d[23]),
        "+f"(d[24]), "+f"(d[25]), "+f"(d[26]), "+f"(d[27]), "+f"(d[28]), "+f"(d[29]), "+f"(d[30]), "+f"(d[31]),
        "+f"(d[32]), "+f"(d[33]), "+f"(d[34]), "+f"(d[35]), "+f"(d[36]), "+f"(d[37]), "+f"(d[38]), "+f"(d[39]),
        "+f"(d[40]), "+f"(d[41]), "+f"(d[42]), "+f"(d[43]), "+f"(d[44]), "+f"(d[45]), "+f"(d[46]), "+f"(d[47]),
        "+f"(d[48]), "+f"(d[49]), "+f"(d[50]), "+f"(d[51]), "+f"(d[52]), "+f"(d[53]), "+f"(d[54]), "+f"(d[55]),
        "+f"(d[56]), "+f"(d[57]), "+f"(d[58]), "+f"(d[59]), "+f"(d[60]), "+f"(d[61]), "+f"(d[62]), "+f"(d[63]),
        "+f"(d[64]), "+f"(d[65]), "+f"(d[66]), "+f"(d[67]), "+f"(d[68]), "+f"(d[69]), "+f"(d[70]), "+f"(d[71]),
        "+f"(d[72]), "+f"(d[73]), "+f"(d[74]), "+f"(d[75]), "+f"(d[76]), "+f"(d[77]), "+f"(d[78]), "+f"(d[79]),
        "+f"(d[80]), "+f"(d[81]), "+f"(d[82]), "+f"(d[83]), "+f"(d[84]), "+f"(d[85]), "+f"(d[86]), "+f"(d[87]),
        "+f"(d[88]), "+f"(d[89]), "+f"(d[90]), "+f"(d[91]), "+f"(d[92]), "+f"(d[93]), "+f"(d[94]), "+f"(d[95])
      : "l"(da), "l"(db), "r"(acc));
}

__device__ __forceinline__ void wgmma_n80(float (&d)[40], uint64_t da, uint64_t db, int acc) {
  asm volatile(
      "{.reg .pred p; setp.ne.b32 p, %42, 0;\n"
      "wgmma.mma_async.sync.aligned.m64n80k16.f32.bf16.bf16 {"
      "%0,%1,%2,%3,%4,%5,%6,%7,%8,%9,%10,%11,%12,%13,%14,%15,"
      "%16,%17,%18,%19,%20,%21,%22,%23,%24,%25,%26,%27,%28,%29,%30,%31,"
      "%32,%33,%34,%35,%36,%37,%38,%39"
      "}, %40, %41, p, 1, 1, 0, 1;}\n"
      :
        "+f"(d[0]), "+f"(d[1]), "+f"(d[2]), "+f"(d[3]), "+f"(d[4]), "+f"(d[5]), "+f"(d[6]), "+f"(d[7]),
        "+f"(d[8]), "+f"(d[9]), "+f"(d[10]), "+f"(d[11]), "+f"(d[12]), "+f"(d[13]), "+f"(d[14]), "+f"(d[15]),
        "+f"(d[16]), "+f"(d[17]), "+f"(d[18]), "+f"(d[19]), "+f"(d[20]), "+f"(d[21]), "+f"(d[22]), "+f"(d[23]),
        "+f"(d[24]), "+f"(d[25]), "+f"(d[26]), "+f"(d[27]), "+f"(d[28]), "+f"(d[29]), "+f"(d[30]), "+f"(d[31]),
        "+f"(d[32]), "+f"(d[33]), "+f"(d[34]), "+f"(d[35]), "+f"(d[36]), "+f"(d[37]), "+f"(d[38]), "+f"(d[39])
      : "l"(da), "l"(db), "r"(acc));
}

__device__ __forceinline__ void wgmma_n192_rs(float (&d)[96], const uint32_t (&a)[4], uint64_t db) {
  asm volatile(
      "wgmma.mma_async.sync.aligned.m64n192k16.f32.bf16.bf16 {"
      "%0,%1,%2,%3,%4,%5,%6,%7,%8,%9,%10,%11,%12,%13,%14,%15,"
      "%16,%17,%18,%19,%20,%21,%22,%23,%24,%25,%26,%27,%28,%29,%30,%31,"
      "%32,%33,%34,%35,%36,%37,%38,%39,%40,%41,%42,%43,%44,%45,%46,%47,"
      "%48,%49,%50,%51,%52,%53,%54,%55,%56,%57,%58,%59,%60,%61,%62,%63,"
      "%64,%65,%66,%67,%68,%69,%70,%71,%72,%73,%74,%75,%76,%77,%78,%79,"
      "%80,%81,%82,%83,%84,%85,%86,%87,%88,%89,%90,%91,%92,%93,%94,%95"
      "}, {%96,%97,%98,%99}, %100, 1, 1, 1, 0;\n"
      :
        "+f"(d[0]), "+f"(d[1]), "+f"(d[2]), "+f"(d[3]), "+f"(d[4]), "+f"(d[5]), "+f"(d[6]), "+f"(d[7]),
        "+f"(d[8]), "+f"(d[9]), "+f"(d[10]), "+f"(d[11]), "+f"(d[12]), "+f"(d[13]), "+f"(d[14]), "+f"(d[15]),
        "+f"(d[16]), "+f"(d[17]), "+f"(d[18]), "+f"(d[19]), "+f"(d[20]), "+f"(d[21]), "+f"(d[22]), "+f"(d[23]),
        "+f"(d[24]), "+f"(d[25]), "+f"(d[26]), "+f"(d[27]), "+f"(d[28]), "+f"(d[29]), "+f"(d[30]), "+f"(d[31]),
        "+f"(d[32]), "+f"(d[33]), "+f"(d[34]), "+f"(d[35]), "+f"(d[36]), "+f"(d[37]), "+f"(d[38]), "+f"(d[39]),
        "+f"(d[40]), "+f"(d[41]), "+f"(d[42]), "+f"(d[43]), "+f"(d[44]), "+f"(d[45]), "+f"(d[46]), "+f"(d[47]),
        "+f"(d[48]), "+f"(d[49]), "+f"(d[50]), "+f"(d[51]), "+f"(d[52]), "+f"(d[53]), "+f"(d[54]), "+f"(d[55]),
        "+f"(d[56]), "+f"(d[57]), "+f"(d[58]), "+f"(d[59]), "+f"(d[60]), "+f"(d[61]), "+f"(d[62]), "+f"(d[63]),
        "+f"(d[64]), "+f"(d[65]), "+f"(d[66]), "+f"(d[67]), "+f"(d[68]), "+f"(d[69]), "+f"(d[70]), "+f"(d[71]),
        "+f"(d[72]), "+f"(d[73]), "+f"(d[74]), "+f"(d[75]), "+f"(d[76]), "+f"(d[77]), "+f"(d[78]), "+f"(d[79]),
        "+f"(d[80]), "+f"(d[81]), "+f"(d[82]), "+f"(d[83]), "+f"(d[84]), "+f"(d[85]), "+f"(d[86]), "+f"(d[87]),
        "+f"(d[88]), "+f"(d[89]), "+f"(d[90]), "+f"(d[91]), "+f"(d[92]), "+f"(d[93]), "+f"(d[94]), "+f"(d[95])
      : "r"(a[0]), "r"(a[1]), "r"(a[2]), "r"(a[3]), "l"(db));
}

template <int N> __device__ __forceinline__ void cv_rs(float (&d)[64], const uint32_t (&a)[4], uint64_t db, int acc);
template <> __device__ __forceinline__ void cv_rs<128>(float (&d)[64], const uint32_t (&a)[4], uint64_t db, int acc) {
  asm volatile(
      "{.reg .pred p; setp.ne.b32 p, %69, 0;\n"
      "wgmma.mma_async.sync.aligned.m64n128k16.f32.f16.f16 {"
      "%0,%1,%2,%3,%4,%5,%6,%7,%8,%9,%10,%11,%12,%13,%14,%15,"
      "%16,%17,%18,%19,%20,%21,%22,%23,%24,%25,%26,%27,%28,%29,%30,%31,"
      "%32,%33,%34,%35,%36,%37,%38,%39,%40,%41,%42,%43,%44,%45,%46,%47,"
      "%48,%49,%50,%51,%52,%53,%54,%55,%56,%57,%58,%59,%60,%61,%62,%63"
      "}, {%64,%65,%66,%67}, %68, p, 1, 1, 0;}\n"
      :
        "+f"(d[0]), "+f"(d[1]), "+f"(d[2]), "+f"(d[3]), "+f"(d[4]), "+f"(d[5]), "+f"(d[6]), "+f"(d[7]),
        "+f"(d[8]), "+f"(d[9]), "+f"(d[10]), "+f"(d[11]), "+f"(d[12]), "+f"(d[13]), "+f"(d[14]), "+f"(d[15]),
        "+f"(d[16]), "+f"(d[17]), "+f"(d[18]), "+f"(d[19]), "+f"(d[20]), "+f"(d[21]), "+f"(d[22]), "+f"(d[23]),
        "+f"(d[24]), "+f"(d[25]), "+f"(d[26]), "+f"(d[27]), "+f"(d[28]), "+f"(d[29]), "+f"(d[30]), "+f"(d[31]),
        "+f"(d[32]), "+f"(d[33]), "+f"(d[34]), "+f"(d[35]), "+f"(d[36]), "+f"(d[37]), "+f"(d[38]), "+f"(d[39]),
        "+f"(d[40]), "+f"(d[41]), "+f"(d[42]), "+f"(d[43]), "+f"(d[44]), "+f"(d[45]), "+f"(d[46]), "+f"(d[47]),
        "+f"(d[48]), "+f"(d[49]), "+f"(d[50]), "+f"(d[51]), "+f"(d[52]), "+f"(d[53]), "+f"(d[54]), "+f"(d[55]),
        "+f"(d[56]), "+f"(d[57]), "+f"(d[58]), "+f"(d[59]), "+f"(d[60]), "+f"(d[61]), "+f"(d[62]), "+f"(d[63])
      : "r"(a[0]), "r"(a[1]), "r"(a[2]), "r"(a[3]), "l"(db), "r"(acc));
}

template <> __device__ __forceinline__ void cv_rs<112>(float (&d)[64], const uint32_t (&a)[4], uint64_t db, int acc) {
  asm volatile(
      "{.reg .pred p; setp.ne.b32 p, %61, 0;\n"
      "wgmma.mma_async.sync.aligned.m64n112k16.f32.f16.f16 {"
      "%0,%1,%2,%3,%4,%5,%6,%7,%8,%9,%10,%11,%12,%13,%14,%15,"
      "%16,%17,%18,%19,%20,%21,%22,%23,%24,%25,%26,%27,%28,%29,%30,%31,"
      "%32,%33,%34,%35,%36,%37,%38,%39,%40,%41,%42,%43,%44,%45,%46,%47,"
      "%48,%49,%50,%51,%52,%53,%54,%55"
      "}, {%56,%57,%58,%59}, %60, p, 1, 1, 0;}\n"
      :
        "+f"(d[0]), "+f"(d[1]), "+f"(d[2]), "+f"(d[3]), "+f"(d[4]), "+f"(d[5]), "+f"(d[6]), "+f"(d[7]),
        "+f"(d[8]), "+f"(d[9]), "+f"(d[10]), "+f"(d[11]), "+f"(d[12]), "+f"(d[13]), "+f"(d[14]), "+f"(d[15]),
        "+f"(d[16]), "+f"(d[17]), "+f"(d[18]), "+f"(d[19]), "+f"(d[20]), "+f"(d[21]), "+f"(d[22]), "+f"(d[23]),
        "+f"(d[24]), "+f"(d[25]), "+f"(d[26]), "+f"(d[27]), "+f"(d[28]), "+f"(d[29]), "+f"(d[30]), "+f"(d[31]),
        "+f"(d[32]), "+f"(d[33]), "+f"(d[34]), "+f"(d[35]), "+f"(d[36]), "+f"(d[37]), "+f"(d[38]), "+f"(d[39]),
        "+f"(d[40]), "+f"(d[41]), "+f"(d[42]), "+f"(d[43]), "+f"(d[44]), "+f"(d[45]), "+f"(d[46]), "+f"(d[47]),
        "+f"(d[48]), "+f"(d[49]), "+f"(d[50]), "+f"(d[51]), "+f"(d[52]), "+f"(d[53]), "+f"(d[54]), "+f"(d[55])
      : "r"(a[0]), "r"(a[1]), "r"(a[2]), "r"(a[3]), "l"(db), "r"(acc));
}

template <> __device__ __forceinline__ void cv_rs<96>(float (&d)[64], const uint32_t (&a)[4], uint64_t db, int acc) {
  asm volatile(
      "{.reg .pred p; setp.ne.b32 p, %53, 0;\n"
      "wgmma.mma_async.sync.aligned.m64n96k16.f32.f16.f16 {"
      "%0,%1,%2,%3,%4,%5,%6,%7,%8,%9,%10,%11,%12,%13,%14,%15,"
      "%16,%17,%18,%19,%20,%21,%22,%23,%24,%25,%26,%27,%28,%29,%30,%31,"
      "%32,%33,%34,%35,%36,%37,%38,%39,%40,%41,%42,%43,%44,%45,%46,%47"
      "}, {%48,%49,%50,%51}, %52, p, 1, 1, 0;}\n"
      :
        "+f"(d[0]), "+f"(d[1]), "+f"(d[2]), "+f"(d[3]), "+f"(d[4]), "+f"(d[5]), "+f"(d[6]), "+f"(d[7]),
        "+f"(d[8]), "+f"(d[9]), "+f"(d[10]), "+f"(d[11]), "+f"(d[12]), "+f"(d[13]), "+f"(d[14]), "+f"(d[15]),
        "+f"(d[16]), "+f"(d[17]), "+f"(d[18]), "+f"(d[19]), "+f"(d[20]), "+f"(d[21]), "+f"(d[22]), "+f"(d[23]),
        "+f"(d[24]), "+f"(d[25]), "+f"(d[26]), "+f"(d[27]), "+f"(d[28]), "+f"(d[29]), "+f"(d[30]), "+f"(d[31]),
        "+f"(d[32]), "+f"(d[33]), "+f"(d[34]), "+f"(d[35]), "+f"(d[36]), "+f"(d[37]), "+f"(d[38]), "+f"(d[39]),
        "+f"(d[40]), "+f"(d[41]), "+f"(d[42]), "+f"(d[43]), "+f"(d[44]), "+f"(d[45]), "+f"(d[46]), "+f"(d[47])
      : "r"(a[0]), "r"(a[1]), "r"(a[2]), "r"(a[3]), "l"(db), "r"(acc));
}

template <> __device__ __forceinline__ void cv_rs<80>(float (&d)[64], const uint32_t (&a)[4], uint64_t db, int acc) {
  asm volatile(
      "{.reg .pred p; setp.ne.b32 p, %45, 0;\n"
      "wgmma.mma_async.sync.aligned.m64n80k16.f32.f16.f16 {"
      "%0,%1,%2,%3,%4,%5,%6,%7,%8,%9,%10,%11,%12,%13,%14,%15,"
      "%16,%17,%18,%19,%20,%21,%22,%23,%24,%25,%26,%27,%28,%29,%30,%31,"
      "%32,%33,%34,%35,%36,%37,%38,%39"
      "}, {%40,%41,%42,%43}, %44, p, 1, 1, 0;}\n"
      :
        "+f"(d[0]), "+f"(d[1]), "+f"(d[2]), "+f"(d[3]), "+f"(d[4]), "+f"(d[5]), "+f"(d[6]), "+f"(d[7]),
        "+f"(d[8]), "+f"(d[9]), "+f"(d[10]), "+f"(d[11]), "+f"(d[12]), "+f"(d[13]), "+f"(d[14]), "+f"(d[15]),
        "+f"(d[16]), "+f"(d[17]), "+f"(d[18]), "+f"(d[19]), "+f"(d[20]), "+f"(d[21]), "+f"(d[22]), "+f"(d[23]),
        "+f"(d[24]), "+f"(d[25]), "+f"(d[26]), "+f"(d[27]), "+f"(d[28]), "+f"(d[29]), "+f"(d[30]), "+f"(d[31]),
        "+f"(d[32]), "+f"(d[33]), "+f"(d[34]), "+f"(d[35]), "+f"(d[36]), "+f"(d[37]), "+f"(d[38]), "+f"(d[39])
      : "r"(a[0]), "r"(a[1]), "r"(a[2]), "r"(a[3]), "l"(db), "r"(acc));
}

template <> __device__ __forceinline__ void cv_rs<64>(float (&d)[64], const uint32_t (&a)[4], uint64_t db, int acc) {
  asm volatile(
      "{.reg .pred p; setp.ne.b32 p, %37, 0;\n"
      "wgmma.mma_async.sync.aligned.m64n64k16.f32.f16.f16 {"
      "%0,%1,%2,%3,%4,%5,%6,%7,%8,%9,%10,%11,%12,%13,%14,%15,"
      "%16,%17,%18,%19,%20,%21,%22,%23,%24,%25,%26,%27,%28,%29,%30,%31"
      "}, {%32,%33,%34,%35}, %36, p, 1, 1, 0;}\n"
      :
        "+f"(d[0]), "+f"(d[1]), "+f"(d[2]), "+f"(d[3]), "+f"(d[4]), "+f"(d[5]), "+f"(d[6]), "+f"(d[7]),
        "+f"(d[8]), "+f"(d[9]), "+f"(d[10]), "+f"(d[11]), "+f"(d[12]), "+f"(d[13]), "+f"(d[14]), "+f"(d[15]),
        "+f"(d[16]), "+f"(d[17]), "+f"(d[18]), "+f"(d[19]), "+f"(d[20]), "+f"(d[21]), "+f"(d[22]), "+f"(d[23]),
        "+f"(d[24]), "+f"(d[25]), "+f"(d[26]), "+f"(d[27]), "+f"(d[28]), "+f"(d[29]), "+f"(d[30]), "+f"(d[31])
      : "r"(a[0]), "r"(a[1]), "r"(a[2]), "r"(a[3]), "l"(db), "r"(acc));
}

__device__ __forceinline__ void cv_ss64(float (&d)[64], uint64_t da, uint64_t db) {
  asm volatile(
      "wgmma.mma_async.sync.aligned.m64n64k16.f32.f16.f16 {"
      "%0,%1,%2,%3,%4,%5,%6,%7,%8,%9,%10,%11,%12,%13,%14,%15,"
      "%16,%17,%18,%19,%20,%21,%22,%23,%24,%25,%26,%27,%28,%29,%30,%31"
      "}, %32, %33, 1, 1, 1, 1, 0;\n"
      :
        "+f"(d[0]), "+f"(d[1]), "+f"(d[2]), "+f"(d[3]), "+f"(d[4]), "+f"(d[5]), "+f"(d[6]), "+f"(d[7]),
        "+f"(d[8]), "+f"(d[9]), "+f"(d[10]), "+f"(d[11]), "+f"(d[12]), "+f"(d[13]), "+f"(d[14]), "+f"(d[15]),
        "+f"(d[16]), "+f"(d[17]), "+f"(d[18]), "+f"(d[19]), "+f"(d[20]), "+f"(d[21]), "+f"(d[22]), "+f"(d[23]),
        "+f"(d[24]), "+f"(d[25]), "+f"(d[26]), "+f"(d[27]), "+f"(d[28]), "+f"(d[29]), "+f"(d[30]), "+f"(d[31])
      : "l"(da), "l"(db));
}

__device__ __forceinline__ void cv_ss32(float (&d)[64], uint64_t da, uint64_t db) {
  asm volatile(
      "wgmma.mma_async.sync.aligned.m64n32k16.f32.f16.f16 {"
      "%0,%1,%2,%3,%4,%5,%6,%7,%8,%9,%10,%11,%12,%13,%14,%15"
      "}, %16, %17, 1, 1, 1, 1, 0;\n"
      :
        "+f"(d[0]), "+f"(d[1]), "+f"(d[2]), "+f"(d[3]), "+f"(d[4]), "+f"(d[5]), "+f"(d[6]), "+f"(d[7]),
        "+f"(d[8]), "+f"(d[9]), "+f"(d[10]), "+f"(d[11]), "+f"(d[12]), "+f"(d[13]), "+f"(d[14]), "+f"(d[15])
      : "l"(da), "l"(db));
}

__device__ __forceinline__ void wgmma_n8_ta(float (&d)[4], uint64_t da, uint64_t db) {
  asm volatile(
      "wgmma.mma_async.sync.aligned.m64n8k16.f32.bf16.bf16 {"
      "%0,%1,%2,%3"
      "}, %4, %5, 1, 1, 1, 1, 0;\n"
      :
        "+f"(d[0]), "+f"(d[1]), "+f"(d[2]), "+f"(d[3])
      : "l"(da), "l"(db));
}

__device__ __forceinline__ void mma16816(float (&d)[4], uint32_t a0, uint32_t a1, uint32_t a2, uint32_t a3, uint32_t b0,
                                         uint32_t b1) {
  asm("mma.sync.aligned.m16n8k16.row.col.f32.f16.f16.f32 {%0,%1,%2,%3},{%4,%5,%6,%7},{%8,%9},{%0,%1,%2,%3};"
      : "+f"(d[0]), "+f"(d[1]), "+f"(d[2]), "+f"(d[3]) : "r"(a0), "r"(a1), "r"(a2), "r"(a3), "r"(b0), "r"(b1));
}
__device__ __forceinline__ void mma16816b(float (&d)[4], uint32_t a0, uint32_t a1, uint32_t a2, uint32_t a3, uint32_t b0,
                                          uint32_t b1) {
  asm("mma.sync.aligned.m16n8k16.row.col.f32.bf16.bf16.f32 {%0,%1,%2,%3},{%4,%5,%6,%7},{%8,%9},{%0,%1,%2,%3};"
      : "+f"(d[0]), "+f"(d[1]), "+f"(d[2]), "+f"(d[3]) : "r"(a0), "r"(a1), "r"(a2), "r"(a3), "r"(b0), "r"(b1));
}
__device__ __forceinline__ void ldsm4(uint32_t a, uint32_t& r0, uint32_t& r1, uint32_t& r2, uint32_t& r3) {
  asm volatile("ldmatrix.sync.aligned.m8n8.x4.shared.b16 {%0,%1,%2,%3}, [%4];"
               : "=r"(r0), "=r"(r1), "=r"(r2), "=r"(r3) : "r"(a) : "memory");
}
__device__ __forceinline__ void ldsm1(uint32_t a, uint32_t& r0) {
  asm volatile("ldmatrix.sync.aligned.m8n8.x1.shared.b16 {%0}, [%1];" : "=r"(r0) : "r"(a) : "memory");
}
__device__ __forceinline__ void ldsm4t(uint32_t a, uint32_t& r0, uint32_t& r1, uint32_t& r2, uint32_t& r3) {
  asm volatile("ldmatrix.sync.aligned.m8n8.x4.trans.shared.b16 {%0,%1,%2,%3}, [%4];"
               : "=r"(r0), "=r"(r1), "=r"(r2), "=r"(r3) : "r"(a) : "memory");
}
__device__ __forceinline__ void stsm4(uint32_t a, uint32_t r0, uint32_t r1, uint32_t r2, uint32_t r3) {
  asm volatile("stmatrix.sync.aligned.m8n8.x4.shared.b16 [%0], {%1,%2,%3,%4};" ::"r"(a), "r"(r0), "r"(r1), "r"(r2), "r"(r3)
               : "memory");
}
__device__ __forceinline__ void stsm2(uint32_t a, uint32_t r0, uint32_t r1) {
  asm volatile("stmatrix.sync.aligned.m8n8.x2.shared.b16 [%0], {%1,%2};" ::"r"(a), "r"(r0), "r"(r1) : "memory");
}
__device__ __forceinline__ uint32_t lds32(uint32_t a) {
  uint32_t v; asm volatile("ld.shared.u32 %0, [%1];" : "=r"(v) : "r"(a) : "memory"); return v;
}
__device__ __forceinline__ float ldsf(uint32_t a) { return __uint_as_float(lds32(a)); }
__device__ __forceinline__ uint2 lds64(uint32_t a) {
  uint2 v; asm volatile("ld.shared.v2.u32 {%0,%1}, [%2];" : "=r"(v.x), "=r"(v.y) : "r"(a) : "memory"); return v;
}
__device__ __forceinline__ uint4 lds128(uint32_t a) {
  uint4 v;
  asm volatile("ld.shared.v4.u32 {%0,%1,%2,%3}, [%4];" : "=r"(v.x), "=r"(v.y), "=r"(v.z), "=r"(v.w) : "r"(a) : "memory");
  return v;
}
__device__ __forceinline__ void sts32(uint32_t a, uint32_t v) { asm volatile("st.shared.u32 [%0], %1;" ::"r"(a), "r"(v) : "memory"); }
__device__ __forceinline__ void sts16(uint32_t a, uint32_t v) {
  asm volatile("st.shared.u16 [%0], %1;" ::"r"(a), "h"((uint16_t)v) : "memory");
}
__device__ __forceinline__ void sts64(uint32_t a, uint32_t x, uint32_t y) {
  asm volatile("st.shared.v2.u32 [%0], {%1,%2};" ::"r"(a), "r"(x), "r"(y) : "memory");
}
__device__ __forceinline__ void sts64f(uint32_t a, float x, float y) { sts64(a, __float_as_uint(x), __float_as_uint(y)); }
__device__ __forceinline__ void sts128(uint32_t a, uint32_t x, uint32_t y, uint32_t z, uint32_t w) {
  asm volatile("st.shared.v4.u32 [%0], {%1,%2,%3,%4};" ::"r"(a), "r"(x), "r"(y), "r"(z), "r"(w) : "memory");
}
__device__ __forceinline__ uint32_t pack_h2(float lo, float hi) {
  uint32_t r; asm("cvt.rn.f16x2.f32 %0, %1, %2;" : "=r"(r) : "f"(hi), "f"(lo)); return r;
}
__device__ __forceinline__ uint32_t pack_b2(float lo, float hi) {
  uint32_t r; asm("cvt.rn.bf16x2.f32 %0, %1, %2;" : "=r"(r) : "f"(hi), "f"(lo)); return r;
}
__device__ __forceinline__ uint32_t hadd2(uint32_t a, uint32_t b) {
  uint32_t r; asm("add.rn.f16x2 %0, %1, %2;" : "=r"(r) : "r"(a), "r"(b)); return r;
}
__device__ __forceinline__ uint32_t hmul2(uint32_t a, uint32_t b) {
  uint32_t r; asm("mul.rn.f16x2 %0, %1, %2;" : "=r"(r) : "r"(a), "r"(b)); return r;
}
__device__ __forceinline__ uint32_t hfma2(uint32_t a, uint32_t b, uint32_t c) {
  uint32_t r; asm("fma.rn.f16x2 %0, %1, %2, %3;" : "=r"(r) : "r"(a), "r"(b), "r"(c)); return r;
}
__device__ __forceinline__ uint32_t hfnma2(uint32_t a, uint32_t b, uint32_t c) {
  uint32_t r;
  asm("{.reg .b32 t; neg.f16x2 t, %1; fma.rn.f16x2 %0, t, %2, %3;}" : "=r"(r) : "r"(a), "r"(b), "r"(c));
  return r;
}
__device__ __forceinline__ uint32_t bfma2(uint32_t a, uint32_t b, uint32_t c) {
  uint32_t r; asm("fma.rn.bf16x2 %0, %1, %2, %3;" : "=r"(r) : "r"(a), "r"(b), "r"(c)); return r;
}
__device__ __forceinline__ float bf_lo(uint32_t v) { return __uint_as_float(v << 16); }
__device__ __forceinline__ float bf_hi(uint32_t v) { return __uint_as_float(v & 0xffff0000u); }
__device__ __forceinline__ float bf_round(float v) { return __bfloat162float(__float2bfloat16_rn(v)); }
__device__ __forceinline__ float tanh_fast(float v) { float r; asm("tanh.approx.f32 %0, %1;" : "=f"(r) : "f"(v)); return r; }
__device__ __forceinline__ float ex2_fast(float v) { float r; asm("ex2.approx.ftz.f32 %0, %1;" : "=f"(r) : "f"(v)); return r; }
__device__ __forceinline__ uint32_t ldg32(const void* p) {
  uint32_t v; asm volatile("ld.global.nc.u32 %0, [%1];" : "=r"(v) : "l"(p)); return v;
}

__device__ __forceinline__ uint32_t ldg16(const void* p) {
  uint16_t v; asm volatile("ld.global.nc.u16 %0, [%1];" : "=h"(v) : "l"(p)); return v;
}

struct c2 { float r, i; };
__device__ __forceinline__ c2 cmul(c2 a, c2 b) {
  c2 o; o.r = fmaf(-a.i, b.i, a.r * b.r); o.i = fmaf(a.r, b.i, a.i * b.r); return o;
}
__device__ __forceinline__ c2 zpow(float a2, float tau, float e) {
  const float mag = ex2_fast(a2 * e);
  const float k = __fadd_rn(fmaf(tau, e, 12582912.f), -12582912.f);
  const float ang = fmaf(tau, e, -k) * 6.283185307179586f;
  c2 o; o.r = mag * __cosf(ang); o.i = mag * __sinf(ang); return o;
}

__device__ __forceinline__ c2 csq(c2 a) { c2 o; o.r = fmaf(-a.i, a.i, a.r * a.r); o.i = (a.r + a.r) * a.i; return o; }
struct h2 { uint32_t r, i; };
__device__ __forceinline__ h2 hpack(const c2 (&v)[2]) { return h2{pack_h2(v[0].r, v[1].r), pack_h2(v[0].i, v[1].i)}; }
__device__ __forceinline__ h2 hmul(h2 a, h2 b) {
  return h2{hfnma2(a.i, b.i, hmul2(a.r, b.r)), hfma2(a.i, b.r, hmul2(a.r, b.i))};
}

__device__ __forceinline__ void kgen_warp(uint32_t kb, int lane, uint32_t p_are, uint32_t p_aim, uint32_t p_bre,
                                          uint32_t p_bim, uint32_t p_cre, uint32_t p_cim, float dt, uint32_t p_dsk,
                                          uint32_t zero) {
  const float k1 = 1.4426950408889634f, k2 = 0.15915494309189535f;
  const float a2[2] = {(dt * bf_lo(p_are)) * k1, (dt * bf_hi(p_are)) * k1};
  const float tau[2] = {(dt * bf_lo(p_aim)) * k2, (dt * bf_hi(p_aim)) * k2};
  c2 z[2];
  auto seed = [&](float sgn, float e, uint32_t after) {
    e = __uint_as_float(__float_as_uint(e) | (after & zero));
    z[0] = zpow(a2[0], sgn * tau[0], e); z[1] = zpow(a2[1], sgn * tau[1], e); return hpack(z); };
  auto next = [&]() { z[0] = csq(z[0]); z[1] = csq(z[1]); return hpack(z); };
  const h2 z1 = seed(-1.f, 1.f, 0u), z2 = next(), z4 = next();
  c2 W[2];
  W[0] = cmul(c2{bf_lo(p_cre), bf_lo(p_cim)}, c2{bf_lo(p_bre), bf_lo(p_bim)});
  W[1] = cmul(c2{bf_hi(p_cre), bf_hi(p_cim)}, c2{bf_hi(p_bre), bf_hi(p_bim)});
  const float mx = fmaxf(fmaxf(fabsf(W[0].r), fabsf(W[0].i)), fmaxf(fabsf(W[1].r), fabsf(W[1].i)));
  uint32_t eb = __reduce_max_sync(0xffffffffu, __float_as_uint(mx)) >> 23;
  eb = min(max(eb, 14u), 253u);
  const float sc = __uint_as_float((261u - eb) << 23);
#pragma unroll
  for (int m = 0; m < 2; m++) { W[m].r *= sc; W[m].i *= -sc; }
  if (lane == 0) sts128(kb + 2608, eb, __float_as_uint(dt), p_dsk << 16, 0u);

  const uint32_t st = kb + ((lane & 8) + (lane >> 4)) * 144 + (lane & 7) * 16;
  const uint32_t ld = kb + (lane & 15) * 144 + (lane >> 4) * 16;
  auto put = [&](int r, h2 v0, h2 v1) { stsm4(st + r * 144, v0.r, v0.i, v1.r, v1.i); };
  uint32_t bf[3][8][2];
  auto fetch = [&](int nb) {
    __syncwarp();
#pragma unroll
    for (int k = 0; k < 8; k += 2) ldsm4(ld + k * 16, bf[nb][k][0], bf[nb][k][1], bf[nb][k + 1][0], bf[nb][k + 1][1]);
    __syncwarp();
  };
  const h2 w0 = hpack(W);
  const h2 w1 = hmul(w0, z1), w3 = hmul(w1, z2), w2 = hmul(w0, z2), w4 = hmul(w0, z4), w6 = hmul(w2, z4);
  put(0, w0, w1); put(2, w2, w3); const h2 w7 = hmul(w3, z4);
  put(4, w4, hmul(w1, z4)); put(6, w6, w7);
  fetch(0);
  const h2 za = seed(-1.f, 256.f, w7.i), zb = next(), zc = next();
  const h2 v1 = hmul(w0, za), v2 = hmul(w0, zb), v3 = hmul(v1, zb), w260 = hmul(w4, za);
  put(0, v1, hmul(w2, za)); put(2, w260, hmul(w6, za)); const h2 w772 = hmul(w260, zb);
  put(4, v2, hmul(w4, zb)); put(6, v3, w772);
  fetch(1);
  const h2 v4 = hmul(w0, zc);
  const h2 v8 = hmul(v4, zc);
  put(0, v4, hmul(v2, zc)); put(2, hmul(v1, zc), hmul(v3, zc)); stsm2(st + 4 * 144, v8.r, v8.i);
  fetch(2);
  const h2 y1 = seed(1.f, 8.f, w772.i), y2 = next(), y4 = next(), y8 = next();
  sts64(kb + 2304 + lane * 8, y8.r, y8.i);
  const h2 y3 = hmul(y1, y2);
  put(0, h2{0x3C003C00u, 0u}, y1); put(2, y2, y3); put(4, y4, hmul(y1, y4)); put(6, hmul(y2, y4), hmul(y3, y4));
  __syncwarp();
  float acc[6][4];
#pragma unroll
  for (int i = 0; i < 6; i++) acc[i][0] = acc[i][1] = acc[i][2] = acc[i][3] = 0.f;
  const uint32_t l1 = kb + (lane & 7) * 144;
#pragma unroll
  for (int k = 0; k < 8; k++) {
    h2 q0;
    ldsm1(l1 + k * 16, q0.r); ldsm1(l1 + 8 * 144 + k * 16, q0.i);
    const uint2 mu = lds64(kb + 2304 + (k * 4 + (lane & 3)) * 8);
    const h2 q1 = hmul(q0, h2{mu.x, mu.y}), q2 = hmul(q1, h2{mu.x, mu.y}), q3 = hmul(q2, h2{mu.x, mu.y});
#pragma unroll
    for (int nb = 0; nb < 3; nb++) mma16816(acc[nb], q0.r, q1.r, q0.i, q1.i, bf[nb][k][0], bf[nb][k][1]);
#pragma unroll
    for (int nb = 0; nb < 3; nb++) mma16816(acc[3 + nb], q2.r, q3.r, q2.i, q3.i, bf[nb][k][0], bf[nb][k][1]);
  }
  __syncwarp();
  const int g = lane >> 2, c = lane & 3;
  const uint32_t d0 = kb + lane * 4, d2 = kb + (544 + 68 * (g & 1) + (g >> 1) + (c < 2 ? 16 * c : 64)) * 2;
  const uint32_t d1 = kb + (c < 2 ? 128 + 2 * g + c : 192 + 8 * c + g) * 4;
#pragma unroll
  for (int q = 0; q < 4; q++) {
    const int mb = (q >> 1) * 3, o = (q & 1) * 2;
    sts32(d0 + q * 128, pack_h2(acc[mb][o], acc[mb][o + 1]));
    sts32(d1 + q * 64, pack_h2(acc[mb + 1][o], acc[mb + 1][o + 1]));
    const uint32_t v = pack_h2(acc[mb + 2][o], acc[mb + 2][o + 1]);
    if (c < 2 || (q == 0 && lane == 2)) sts16(d2 + q * 8, v);
    if (c < 2) sts16(d2 + q * 8 + 64, v >> 16);
  }
}

struct CvAddr { uint32_t ta, cp, s0, s1, zero; };
__host__ __device__ constexpr int cv_lag(int I) { return (I & 1) * 16 + ((I >> 1) & 1) * 64 + (I >> 2) * 256; }
template <int I>
__device__ __forceinline__ void cv_load(uint32_t (&a)[6][4], uint32_t (&t)[2], const CvAddr& A) {
  constexpr int o = cv_lag(I) * 4, r = I % 6;
  if (I <= 8 || I >= 16) { a[r][0] = lds32(A.ta + o); a[r][2] = lds32(A.ta + o - 8); }
  else {
    asm volatile("prmt.b32 %0, %1, 0, %2;" : "=r"(a[r][0]) : "r"(t[0]), "r"(A.s0));
    asm volatile("prmt.b32 %0, %1, 0, %2;" : "=r"(a[r][2]) : "r"(t[0]), "r"(A.s1));
  }
  if (I < 8) { a[r][1] = lds32(A.ta + o + 512); a[r][3] = lds32(A.ta + o + 504); }
  else if (I < 16) {
    asm volatile("prmt.b32 %0, %1, 0, %2;" : "=r"(a[r][1]) : "r"(t[1]), "r"(A.s0));
    asm volatile("prmt.b32 %0, %1, 0, %2;" : "=r"(a[r][3]) : "r"(t[1]), "r"(A.s1));
  } else {
    asm volatile("and.b32 %0, %1, %2;" : "=r"(a[r][1]) : "r"(A.s0), "r"(A.zero));
    asm volatile("and.b32 %0, %1, %2;" : "=r"(a[r][3]) : "r"(A.s1), "r"(A.zero));
  }
  if (I >= 7 && I < 15) {
    constexpr int on = cv_lag(I + 1);
    if (I > 7) t[0] = lds32(A.cp + on);
    t[1] = lds32(A.cp + on + 128);
  }
}
template <int I>
__device__ __forceinline__ void cv_step(float (&acc)[64], uint32_t (&a)[6][4], uint32_t (&t)[2], const CvAddr& A, uint64_t db) {
  constexpr int dofs = cv_lag(I) / 8;
  wg_fence();
  cv_rs<128 - 16 * (I >> 2)>(acc, a[I % 6], db + dofs, I > 0);
  wg_commit();
  if constexpr (I < 2) { cv_load<2 * I + 2>(a, t, A); cv_load<2 * I + 3>(a, t, A); }
  if constexpr (I >= 2 && I < 14) { wg_wait<2>(); cv_load<I + 4>(a, t, A); }
  if constexpr (I < 17) cv_step<I + 1>(acc, a, t, A, db);
}
__device__ __forceinline__ void conv_channel(int ch, int dglob, int warp, int lane, uint32_t zero) {
  const int g = lane >> 2, c = lane & 3, wq = warp & 3, w0 = wq & 1, hi = wq >> 1;
  const uint32_t tc = SM_T + ch * CB;
  CvAddr A;
  {
    const int o = g - 4 * c, sw = 8 * w0 + 32 * hi;
    auto grp = [](int l) { return ((l + 2) >> 3) + ((l + 5) >> 3); };
    auto sel = [&](int l) { return grp(l) == grp(o) ? 0x10u : 0x32u; };
    A.ta = tc + (32 + sw + o) * 4;
    A.cp = SM_CP + ch * CB + sw + grp(o) * 4;
    A.s0 = 0x10u | (sel(o - 1) << 8);
    A.s1 = sel(o - 2) | (sel(o - 3) << 8);
    A.zero = zero;
  }
  float acc[64];
  uint32_t a[6][4], t[2];
  cv_load<0>(a, t, A);
  cv_load<1>(a, t, A);
  mbar_wait(B_ULD + 8 * ch, 0);
  cv_step<0>(acc, a, t, A, mkdesc(SM_U + ch * CB, 16, 256, 3));
  mbar_wait(B_PREP + 8 * ch, 0);
  if (ch == 3) mbar_wait(B_HST + 8, 0);
  {
    const uint64_t wa = mkdesc(SM_W + ch * CB, W7_OFF, W_PS, 0), wt = mkdesc(tc + 1120 * 4, 1024, 128, 0);
    cv_ss64(acc, wa, wt);
    wg_fence();
    cv_ss32(acc, wa + 8, wt + 32);
  }
  wg_commit();
  const float inv = ldsf(tc + NTW * 4);
  const int bar = 4 + (warp >> 2), p = 63 - c + hi, wv = 2 * (p & 3) + w0;
  const uint32_t ob = ch == 3 ? SM_CS : SM_O + ch * CB;
  const uint32_t oa = ob + (p >> 2) * 256 + ((wv ^ ((dglob >> 1) & 3) ^ (wv >> 2)) << 5) + g * 4;
  wg_wait<0>();
#pragma unroll
  for (int j = 0; j < 15; j++) { acc[4 * j] += acc[4 * j + 6]; acc[4 * j + 1] += acc[4 * j + 7]; }
  auto send = [&](int j) { sts32(oa - j * 256, pack_b2(acc[4 * j + 1] * inv, acc[4 * j] * inv)); };
  auto fin = [&](int j) {
    const uint32_t r = lds32(oa - j * 256);
    sts32(oa - j * 256, pack_b2(fmaf(acc[4 * j + 1], inv, bf_lo(r)), fmaf(acc[4 * j], inv, bf_hi(r))));
  };
  if (hi) {
#pragma unroll
    for (int j = 8; j < 16; j++) send(j);
    if (c == 0) sts32(oa - 16 * 256, 0u);
    bar_sync(bar + 4, 128);
#pragma unroll
    for (int j = 0; j < 8; j++)
      if (j > 0 || c > 0) fin(j);
  } else {
#pragma unroll
    for (int j = 0; j < 8; j++)
      if (j < 7 || c < 3) send(j);
    bar_sync(bar + 4, 128);
#pragma unroll
    for (int j = 8; j < 16; j++) fin(j);
    if (c == 3) fin(7);
  }
  fence_async_smem();
  __syncwarp();
  if (ch < 3 && lane == 0) mbar_arrive(B_CVD);
}

template <bool USE_SMID>
__global__ void __launch_bounds__(NTHREADS, 1)
s4_ffn_kernel(const Params P, const __grid_constant__ CUtensorMap tmXr, const __grid_constant__ CUtensorMap tmX,
              const __grid_constant__ CUtensorMap tmW1, const __grid_constant__ CUtensorMap tmW2,
              const __grid_constant__ CUtensorMap tmU, const __grid_constant__ CUtensorMap tmXe,
              const __grid_constant__ CUtensorMap tmO, const __grid_constant__ CUtensorMap tmS) {
  extern __shared__ uint8_t smem_raw[];
  const long long t_start = clock64();
  const int tid = threadIdx.x, lane = tid & 31;
  uint32_t vid = blockIdx.x;
  if (USE_SMID) asm("mov.u32 %0, %%smid;" : "=r"(vid));
  const int cta = vid < 120 ? vid : vid - 4;

  uint32_t p_are = 0, p_aim = 0, p_bre = 0, p_bim = 0, p_cre = 0, p_cim = 0, p_ldt = 0, p_dsk = 0;
  if (tid < 480) {
    const int po = cta * 960 + tid * 2, pc = cta * 5 + tid / 96;
    while (tid >= 128 && clock64() - t_start < T_P0 + (tid >> 7) * T_PD) {}
    p_ldt = ldg16(P.logdt + pc);
    p_are = ldg32(P.are + po); p_aim = ldg32(P.aim + po);
    p_cre = ldg32(P.cre + po); p_cim = ldg32(P.cim + po); p_bre = ldg32(P.bre + po); p_bim = ldg32(P.bim + po);
    p_dsk = ldg16(P.dskip + pc);
  }
  const int warp = __shfl_sync(0xffffffffu, tid >> 5, 0);

  if (__builtin_expect(vid >= 120 && vid < 124, 0)) {
    const int hid = vid - 120;
    if (warp == 15) {
      if (elect_one()) {
#pragma unroll
        for (int i = 0; i < 8; i++) mbar_init(SM_BAR + i * 8, i < 4 ? 1 : 8);
        asm volatile("fence.mbarrier_init.release.cluster;" ::: "memory");
      }
      __syncwarp();
      bar_arrive(1, 288);
      if (elect_one()) {
#pragma unroll 1
        for (int k = 0; k < 10; k++) {
          const uint32_t sl = k & 3;
          mbar_wait(SM_BAR + 32 + sl * 8, ((k >> 2) & 1) ^ 1);
          mbar_expect(SM_BAR + sl * 8, 49152);
#pragma unroll
          for (int i = 0; i < 4; i++)
            tma3d(SB + sl * 49152 + i * 12288, &tmW1, 0, k * 64 + (i & 1) * 32, (hid * 2 + (i >> 1)) * 3, SM_BAR + sl * 8);
        }
      }
    } else if (warp < 8) {
      const int wg = warp >> 2;
      if (tid == 32) sts32(SM_EPOCH, atomicAdd(&P.scr->cnt[C_CHK * 32], 1u) / 132 + 1);
      if (tid < 32) sts32(SM_CS + tid * 4, 0x3F803F80u);
      fence_async_smem();
      bar_sync(1, 288);
      float acc[3][4];
#pragma unroll
      for (int i = 0; i < 12; i++) acc[i >> 2][i & 3] = 0.f;
#pragma unroll 1
      for (int k = 0; k < 10; k++) {
        const uint32_t sl = k & 3;
        mbar_wait(SM_BAR + sl * 8, (k >> 2) & 1);
        const uint64_t da = mkdesc(SB + sl * 49152 + wg * 24576, 4096, 1024, 1);
        wg_fence();
#pragma unroll
        for (int i = 0; i < 12; i++)
          wgmma_n8_ta(acc[i % 3], da + (i % 3) * 256 + ((i / 3) & 1) * 128 + (i / 6) * 768, mkdesc(SM_CS, 0, 128, 0));
        wg_commit();
        wg_wait<0>();
        if (lane == 0) mbar_arrive(SM_BAR + 32 + sl * 8);
      }
      if ((lane & 3) < 2) {
#pragma unroll
        for (int i = 0; i < 3; i++) {
          const float t = -((lane & 1) ? acc[i][2] : acc[i][0]), t0 = bf_round(t), t1 = bf_round(t - t0);
          st_tagged(&P.scr->cs[hid * 384 + wg * 192 + i * 64 + (warp & 3) * 16 + (lane & 1) * 8 + (lane >> 2)],
                    pack_b2(t0, t1), pack_b2(0.f, t - t0 - t1), lds32(SM_EPOCH));
        }
      }
    }
    if (tid == 0) {
      if (USE_SMID) poll_flag(&P.scr->cnt[C_CHK * 32], lds32(SM_EPOCH) * 132);
    }
    return;
  }

  int mt, ns;
  if (vid < 64) { mt = vid & 15; ns = vid >> 4; }
  else if (vid < 120) { const int t = vid - 64, q = t / 14; mt = 2 + t - q * 14; ns = 4 + q; }
  else { mt = vid & 1; ns = (vid - 116) >> 1; }

  if (warp == 15) {
    if (elect_one()) {
      tm_prefetch(&tmXr);
      const unsigned chk = atomicAdd(&P.scr->cnt[C_CHK * 32], 1u);
      if ((uint32_t)__cvta_generic_to_shared(smem_raw) != SB) __trap();
#pragma unroll
      for (int i = 0; i < 50; i++) mbar_init(SM_BAR + i * 8, i < 26 ? 1 : (i < 46 ? 2 : (i < 48 ? 8 : (i == 48 ? 12 : 6))));
      asm volatile("fence.mbarrier_init.release.cluster;" ::: "memory");
      mbar_expect(B_XROW, 16 * D_ * 2 + NTW * 4);
#pragma unroll 1
      for (int i = 0; i < 5; i++) {
        while (clock64() - t_start < T_X + min(i, 2) * T_XD) {}
        tma5d(SM_U + i * CB, &tmXr, cta * 2, 2 * i, B_XROW);
      }
      bulk_g2s(SM_T + 4 * CB, P.idx, NTW * 4, B_XROW);
      tm_prefetch(&tmX); tm_prefetch(&tmW1); tm_prefetch(&tmW2); tm_prefetch(&tmU); tm_prefetch(&tmXe); tm_prefetch(&tmO);
      tm_prefetch(&tmS);
      while (clock64() - t_start < T_W1) {}
      bulk_prefetch(P.w1 + (size_t)cta * 3072, 6144);
      bulk_prefetch(P.w1 + 256 * F_ + (size_t)cta * 4608, 9216);
      sts32(SM_EPOCH, chk / 132 + 1);
      while (clock64() - t_start < T_G1) {}
#pragma unroll 1
      for (int k = 0; k < 6; k++) {
        mbar_expect(B_FULL1 + 8 * k, G1_STAGE);
        tma2d(SB + k * G1_STAGE, &tmX, k * 32, mt * 128, B_FULL1 + 8 * k);
        tma3d(SB + k * G1_STAGE + 8192, &tmW1, 0, k * 32, ns * 3, B_FULL1 + 8 * k);
      }
    }
    __syncwarp();
    mbar_wait(B_XROW, 0);
    {
      float ac[4][4];
#pragma unroll
      for (int i = 0; i < 4; i++) ac[i][0] = ac[i][1] = ac[i][2] = ac[i][3] = 0.f;
      const uint32_t la = SM_U + ((lane & 7) + (lane >> 4) * 8) * 128 + ((((lane >> 3) & 1) ^ (lane & 7)) << 4);
      uint32_t a[2][4][4], one[8][2];
#pragma unroll
      for (int i = 0; i < 16; i++) one[i >> 1][i & 1] = 0x3F803F80u ^ ((lane + i) & P.zero);
      auto ld4 = [&](int h, uint32_t o) {
#pragma unroll
        for (int k = 0; k < 4; k++) ldsm4((la ^ (k << 5)) + o, a[h][k][0], a[h][k][1], a[h][k][2], a[h][k][3]);
      };
      auto mm4 = [&](int h) {
#pragma unroll
        for (int k = 0; k < 8; k++) {
          const uint32_t b0 = a[h][k >> 1][(k & 1) * 2], b1 = a[h][k >> 1][(k & 1) * 2 + 1];
          mma16816b(ac[k & 3], b0 ^ P.zero, one[k][0], b1 ^ P.zero, one[k][1], b0, b1);
        }
      };
      ld4(0, 0);
#pragma unroll 1
      for (int i = 0; i < 5; i++) {
        ld4(1, i * CB + 2048);
        mm4(0);
        ld4(0, i * CB + CB);
        mm4(1);
      }
      bar_arrive(2, 512);
      const int src = (lane & 7) * 4 + ((lane & 7) >> 1), odd = (lane >> 2) & 1;
      const float t0 = __shfl_sync(0xffffffffu, odd ? ac[0][1] + ac[2][1] : ac[0][0] + ac[2][0], src);
      const float t1 = __shfl_sync(0xffffffffu, odd ? ac[1][1] + ac[3][1] : ac[1][0] + ac[3][0], src);
      const float m0 = __shfl_sync(0xffffffffu, odd ? ac[0][3] + ac[2][3] : ac[0][2] + ac[2][2], src);
      const float m1 = __shfl_sync(0xffffffffu, odd ? ac[1][3] + ac[3][3] : ac[1][2] + ac[3][2], src);
      const float mean = ((lane & 8) ? m1 : m0) * (1.f / D_);
      float var = fmaf(-mean, mean, ((lane & 8) ? t1 : t0) * (1.f / D_));
      if (mean * mean > 32.f * var) {
        var = 0.f;
#pragma unroll 1
        for (int i = 0; i < D_ / 2; i++) {
          const uint32_t w = lds32(SM_U + (lane & 15) * 128 + (i >> 6) * CB + ((i >> 5) & 1) * 2048 + (i & 31) * 4);
          const float d0 = bf_lo(w) - mean, d1 = bf_hi(w) - mean;
          var = fmaf(d0, d0, fmaf(d1, d1, var));
        }
        var *= 1.f / D_;
      }
      const float mb = bf_round(mean);
      float sd;
      asm("sqrt.approx.ftz.f32 %0, %1;" : "=f"(sd) : "f"(bf_round(bf_round(var) + 1e-5f)));
      const float rs = __fdividef(1.f, bf_round(sd));
      if (lane < 16) {
        const int tok = (lane & 1) + (lane & 2) * 4 + (lane >> 2) * 2;
        st_tagged(&P.scr->stats[cta * 16 + tok], __float_as_uint(0.5f * rs), __float_as_uint(mb), lds32(SM_EPOCH));
        sts64f(SM_LNST + lane * 8, rs, -rs * mb);
      }
      __syncwarp();
    }
    bar_arrive(4, 256);
    if (elect_one()) bulk_prefetch(P.w2 + (size_t)cta * 7680, 15360);
    __syncwarp();

  } else {
    const float dt = bf_round(expf(bf_lo(p_ldt)));
    kgen_warp(SM_W + (warp / 3) * (CB - 3 * KBUF) + warp * KBUF, lane, p_are, p_aim, p_bre, p_bim, p_cre, p_cim, dt, p_dsk, P.zero);
    if (warp < 8) bar_arrive(1, 480);
    else {
      bar_arrive(2, 512);
      constexpr int NW = 7;
      bar_sync(4, 256);
      const uint32_t la = SM_U + (lane & 15) * 128 + (((lane >> 4) ^ (lane & 7)) << 4);
      uint2* uo = reinterpret_cast<uint2*>(P.scr->uT + (127 - cta) * (D_ * 32)) + lane;
      const uint4 sa = lds128(SM_LNST + (lane & 3) * 16), sb = lds128(SM_LNST + (lane & 3) * 16 + 64);
      auto nrm = [&](uint32_t v, const uint4& t) {
        return pack_h2(fmaf(bf_lo(v), __uint_as_float(t.x), __uint_as_float(t.y)), fmaf(bf_hi(v), __uint_as_float(t.z), __uint_as_float(t.w)));
      };
#pragma unroll 1
      for (int i = 14 - warp; i < 40; i += 3 * NW) {
        uint32_t r[3][4];
#pragma unroll
        for (int k = 0; k < 3; k++) {
          const int t = i + NW * k;
          ldsm4t((la ^ ((t & 3) << 5)) + (t >> 3) * CB + (t & 4) * 512, r[k][0], r[k][1], r[k][2], r[k][3]);
        }
#pragma unroll
        for (int k = 0; k < 3; k++) {
          if (i + NW * k < 40) {
            uo[(i + NW * k) * 64] = make_uint2(nrm(r[k][0], sa), nrm(r[k][1], sb));
            uo[(i + NW * k) * 64 + 32] = make_uint2(nrm(r[k][2], sa), nrm(r[k][3], sb));
          }
        }
      }
      bar_sync(1, 480);
    }
  }
  const int g = lane >> 2, c = lane & 3;

  if (warp < 8) {
    float acc[96];
    const uint32_t sta = SM_ST + (warp * 16 + g) * 8;
    {
      const uint64_t da0 = mkdesc(SB + (warp >> 2) * 4096, 16, 512, 2), db0 = mkdesc(SB + 8192, 4096, 1024, 1);
      int s = 0;
      uint32_t ph = 0;
      bar_sync(2, 512);
#pragma unroll 1
      for (int k = 0; k < 20 - AUGK; k++) {
        mbar_wait(B_FULL1 + 8 * s, ph);
        const uint64_t da = da0 + s * (G1_STAGE >> 4), db = db0 + s * (G1_STAGE >> 4);
        wg_fence();
        wgmma_n192(acc, da, db, k);
        wg_commit();
        wg_wait<1>();
        if ((tid & 127) == 0 && k > 0) mbar_arrive(B_EMPTY1 + 8 * (s ? s - 1 : 5));
        wgmma_n192(acc, da + 2, db + 128, 1);
        wg_commit();
        if (++s == 6) { s = 0; ph ^= 1; }
      }
      mbar_wait(B_CST, 0);
      const uint32_t m0 = lds32(sta + 4), m1 = lds32(sta + 68);
      if (AUGK) {
        mbar_wait(B_FULL1 + 8, 1);
        wg_fence();
        wgmma_n192(acc, da0 + (G1_STAGE >> 4), db0 + (G1_STAGE >> 4), 1);
        wgmma_n192(acc, da0 + (G1_STAGE >> 4) + 2, db0 + (G1_STAGE >> 4) + 128, 1);
        wg_commit();
      }
      const uint32_t sel = c == 0 ? 0x3232u : (c == 1 ? 0x4432u : 0x4444u);
      uint32_t am[4];
      asm volatile("prmt.b32 %0, %1, 0, %2;" : "=r"(am[0]) : "r"(m0), "r"(sel));
      asm volatile("prmt.b32 %0, %1, 0, %2;" : "=r"(am[1]) : "r"(m1), "r"(sel));
      asm volatile("and.b32 %0, %1, %2;" : "=r"(am[2]) : "r"(am[0]), "r"(P.zero));
      asm volatile("and.b32 %0, %1, %2;" : "=r"(am[3]) : "r"(am[1]), "r"(P.zero));
      wg_fence();
      wgmma_n192_rs(acc, am, mkdesc(SM_CS, 0, 128, 0));
      wg_commit();
      wg_wait<0>();
    }
    bar_sync(5, 256);
    const int rho = lane & 7;
    const uint32_t sa = SM_HST + ((warp >> 1) * 32 + (lane & 8) * 2 + (warp & 1) * 8 + rho) * 128 + (((lane >> 4) ^ rho) << 4);
    const uint32_t ro = ((warp >> 1) * 32 + (warp & 1) * 8) * 128;
    uint8_t* hg = P.scr->h + (size_t)(mt * 24 + ns * 3) * 16384 + ro;
    auto hstore = [&](int k3) {
      fence_async_smem();
      __syncwarp();
      if (elect_one()) {
        bulk_s2g(hg + k3 * 16384, SM_HST + ro + k3 * G2_SLOT, 1024);
        bulk_s2g(hg + k3 * 16384 + 2048, SM_HST + ro + k3 * G2_SLOT + 2048, 1024);
        bulk_commit();
        if (k3 == 0) mbar_arrive(B_HST);
      }
    };
#pragma unroll
    for (int k3 = 0; k3 < 3; k3++) {
      const float r0 = ldsf(sta), r1 = ldsf(sta + 64);
#pragma unroll
      for (int jj = 0; jj < 8; jj += 2) {
        uint32_t r[4];
#pragma unroll
        for (int h = 0; h < 2; h++) {
          const int j = k3 * 8 + jj + h;
          const float h0 = acc[4 * j] * r0, h1 = acc[4 * j + 1] * r0, h2 = acc[4 * j + 2] * r1, h3 = acc[4 * j + 3] * r1;
          r[2 * h] = pack_b2(fmaf(h0, tanh_fast(h0), h0), fmaf(h1, tanh_fast(h1), h1));
          r[2 * h + 1] = pack_b2(fmaf(h2, tanh_fast(h2), h2), fmaf(h3, tanh_fast(h3), h3));
        }
        if (jj == 0 && k3 > 0) hstore(k3 - 1);
        stsm4((sa ^ (jj << 4)) + k3 * G2_SLOT, r[0], r[1], r[2], r[3]);
      }
    }
    hstore(2);
    bulk_wait0();
    __syncwarp();
    if (lane == 0) mbar_arrive(B_HST + 8);
    if (warp == 4) {
      mbar_wait(B_HST + 8, 0);
      if (elect_one()) {
        red_release(&P.scr->cnt[(C_H + (mt >> 1)) * 32]);
      }
    } else if (warp == 5) {
      if (elect_one()) {
        const uint8_t* wp = P.scr->w2r + (size_t)ns * 24 * 10240;
        poll_flag(&P.scr->cnt[(C_W2 + ns) * 32], lds32(SM_EPOCH) * 16);
        fence_async();
#pragma unroll
        for (int q = 0; q < 4; q++) {
          mbar_expect(B_FULL2 + 8 * q, q < 3 ? 10240 : G2_SLOT);
          bulk_g2s(SB + q * G2_SLOT + 16384, wp + (q < 3 ? ns * 3 + q : (ns ? 0 : 3)) * 10240, 10240, B_FULL2 + 8 * q);
        }
        mbar_wait(B_CVD, 0);
#pragma unroll
        for (int ch = 0; ch < 3; ch++) bulk_s2g(P.scr->s + (cta * 5 + ch) * 1024, SM_O + ch * CB, 4096);
        bulk_commit();
        bulk_wait0_read();
        mbar_arrive(B_FREE);
#pragma unroll
        for (int r = 1; r < 4; r++) {
          mbar_expect(B_FULL2 + 24 + 8 * r, G2_SLOT);
          bulk_g2s(SB + (3 + r) * G2_SLOT + 16384, wp + 3 * (r + (r >= ns)) * 10240, 10240, B_FULL2 + 24 + 8 * r);
        }
        bulk_wait0();
      }
    } else if (warp == 6 && elect_one()) {
      const uint8_t* hp = P.scr->h + (size_t)mt * 24 * 16384;
      poll_flag(&P.scr->cnt[(C_H + (mt >> 1)) * 32], lds32(SM_EPOCH) * 16);
      fence_async();
#pragma unroll
      for (int r = 0; r < 4; r++) {
        if (r == 2) mbar_wait(B_FREE, 0);
        bulk_g2s(SB + (3 + r) * G2_SLOT, hp + 3 * (r + (r >= ns)) * 16384, 16384, B_FULL2 + 24 + 8 * r);
      }
    }
    __syncwarp();
  } else {
    const int at = tid - 256;
    const int tt = warp < 12 ? at : at - 32;
    if (warp == 15) {
      if (elect_one()) {
        {
          int s = 0;
          uint32_t ph = 0;
#pragma unroll 1
          for (int k = 6; k < 20; k++) {
            mbar_wait(B_EMPTY1 + 8 * s, ph);
            mbar_expect(B_FULL1 + 8 * s, G1_STAGE);
            tma2d(SB + s * G1_STAGE, &tmX, k * 32, mt * 128, B_FULL1 + 8 * s);
            tma3d(SB + s * G1_STAGE + 8192, &tmW1, 0, k * 32, ns * 3, B_FULL1 + 8 * s);
            if (++s == 6) { s = 0; ph ^= 1; }
          }
        }
        mbar_arrive(B_G1L);
        mbar_wait(B_W2RD, 0);
        red_release(&P.scr->cnt[(C_W2 + ns) * 32]);
      }
      __syncwarp();
    } else if (warp == 12) {
      if (elect_one()) {
        red_release(&P.scr->cnt[C_U * 32]);
        const unsigned ep = lds32(SM_EPOCH);
        poll_flag(&P.scr->cnt[C_U * 32], ep * 128);
        fence_async();
#pragma unroll 1
        for (int ch = 0; ch < 5; ch++) {
          if (ch == 3) mbar_wait(B_G1L, 0);
          mbar_expect(B_ULD + 8 * ch, UCH);
          tma3d(SM_U + ch * CB, &tmU, 0, 0, cta * 5 + ch, B_ULD + 8 * ch);
        }
      }
      __syncwarp();
    } else {
#pragma unroll 1
      for (int it = tt >> 5; it < 15; it += 6) {
        const int ch = it / 3, oc = min((it - ch * 3) * 31 + lane - 1, 81);
        const uint32_t k0 = SM_W + ch * CB;
        const uint32_t kp = k0 + (oc < 48 ? oc : (oc < 64 ? 52 + (oc & 6) * 2 + ((oc >> 2) & 2) + (oc & 1) : oc + 4)) * 16;
        const uint4 a = lds128(kp), b = lds128(kp + KBUF), d = lds128(kp + 2 * KBUF);
        const uint4 m0 = lds128(k0 + 2608);
        const float dq = __fdividef(__uint_as_float(m0.z), __uint_as_float(m0.y));
        const int e0 = m0.x, e1 = lds32(k0 + KBUF + 2608), e2 = lds32(k0 + 2 * KBUF + 2608);
        const int em = min(max(max(max(e0, e1), e2) + 2, (int)((__float_as_uint(dq) >> 23) & 255) - 6), 254);
        auto ratio = [&](int e) { const float r = __uint_as_float(max(127 + e - em, 0) << 23); return pack_h2(r, r); };
        const uint32_t r0 = ratio(e0), r1 = ratio(e1), r2 = ratio(e2);
        uint32_t x0 = hfma2(a.x, r0, hfma2(b.x, r1, hmul2(d.x, r2)));
        const uint32_t x1 = hfma2(a.y, r0, hfma2(b.y, r1, hmul2(d.y, r2)));
        const uint32_t x2 = hfma2(a.z, r0, hfma2(b.z, r1, hmul2(d.z, r2)));
        const uint32_t x3 = hfma2(a.w, r0, hfma2(b.w, r1, hmul2(d.w, r2)));
        if (oc == 0) x0 = hadd2(x0, pack_h2(dq * __uint_as_float((261 - em) << 23), 0.f));
        const uint32_t xp = __shfl_up_sync(0xffffffffu, oc < 0 ? 0u : x3, 1);
        const uint32_t o = (oc < 32 ? SM_T + 128 : SM_CP - 1024) + ch * CB + oc * 32;
        if (lane > 0) {
          sts128(o, __byte_perm(x0, xp, 0x7610), __byte_perm(x0, 0, 0x1032), __byte_perm(x1, x0, 0x7610), __byte_perm(x1, 0, 0x1032));
          sts128(o + 16, __byte_perm(x2, x1, 0x7610), __byte_perm(x2, 0, 0x1032), __byte_perm(x3, x2, 0x7610), __byte_perm(x3, 0, 0x1032));
        }
        if (oc < 0) sts32(SM_T + ch * CB + NTW * 4, __float_as_uint(__uint_as_float((em - 7) << 23) * __uint_as_float(m0.y)));
      }
      bar_sync(7, 192);
      if (warp == 11) {
        if (elect_one()) {
          fence_async_smem();
          mbar_expect(B_W2LD, 15360);
#pragma unroll 1
          for (int u = 0; u < 3; u++) tma3d(SM_W + (2 + u) * CB, &tmW2, 0, (mt * 3 + u) * 32, ns * 5, B_W2LD);
        }
        __syncwarp();
      }
      uint32_t wo = SM_T + (tt < 16 ? tt + 16 : tt + 272) * 4, ix = lds32(wo + 4 * CB);
#pragma unroll 1
      for (int e = tt; e < 912; e += 192) {
        const uint32_t src = SM_CP + (ix & 0xffffu), sel = ix >> 16, wn = SM_T + (e + 192 + (e < 128 ? 272 : 720)) * 4;
        uint32_t v[5];
#pragma unroll
        for (int ch = 0; ch < 5; ch++) v[ch] = lds32(src + ch * CB);
        ix = lds32(wn + 4 * CB);
#pragma unroll
        for (int ch = 0; ch < 5; ch++) sts32(wo + ch * CB, __byte_perm(v[ch], 0u, sel));
        wo = wn;
      }
      fence_async_smem();
      __syncwarp();
      if (lane == 0) mbar_arrive(B_TAB);
      if (warp == 11) {
        if (elect_one()) {
          mbar_wait(B_W2LD, 0);
#pragma unroll 1
          for (int u = 0; u < 3; u++) bulk_s2g(P.scr->w2r + (size_t)ns * 24 * 10240 + (mt * 3 + u) * 5120, SM_W + (2 + u) * CB, 5120);
          bulk_commit();
          bulk_wait0();
          mbar_arrive(B_W2RD);
        }
        __syncwarp();
      }
      if (warp >= 13) {
        const int t = tid - 13 * 32;
        const uint32_t tag = lds32(SM_EPOCH) & 0xffffu;
        unsigned long long v[5];
        for (int n = 0; n < 20000; n++) {
          bool ok = true;
#pragma unroll
          for (int i = 0; i < 5; i++) {
            v[i] = ld_relaxed(i < 2 ? P.scr->stats + mt * 128 + i * 64 + t : P.scr->cs + ns * 192 + (i - 2) * 64 + t);
            ok = ok && ((uint32_t)(v[i] >> 32) & 0xffffu) == tag;
          }
          if (ok) break;
        }
#pragma unroll
        for (int i = 0; i < 5; i++) {
          if (i < 2) sts64(SM_ST + (i * 64 + t) * 8, (uint32_t)v[i], (uint32_t)(v[i] >> 32));
          else sts128(SM_CS + ((i - 2) * 64 + t) * 16, (uint32_t)v[i], (uint32_t)(v[i] >> 48), 0u, 0u);
        }
        fence_async_smem();
        __syncwarp();
        if (lane == 0) mbar_arrive(B_CST);
      }
    }
  }

  if (warp >= 12) {
    mbar_wait(B_TAB, 0);
    auto uaddr = [&](int r) { return SM_U + r * 32 + ((r & 4) << 2); };
    auto waddr = [&](int e) {
      return SM_W + ((e & 4) + (e & 1) * 2 + ((e >> 4) & 1)) * W_PS + ((e >> 5) * 4 + ((e >> 2) & 2) + ((e >> 1) & 1)) * 16;
    };
    const uint32_t ub0 = uaddr(128 - lane), uc0 = uaddr(127 - lane), oa0 = waddr(2 * lane), ob0 = waddr(2 * lane + 2);
    int prev = -1;
#pragma unroll 1
    for (int it = warp == 15 ? 9 : warp - 12; it < (warp == 15 ? 10 : 9); it += 3) {
      const int ch = it >> 1, q = it & 1;
      const uint32_t ub = ub0 + ch * CB - q * 1024, uc = uc0 + ch * CB - q * 1024;
      mbar_wait(B_ULD + 8 * ch, 0);
      if (ch >= 2) mbar_wait(B_W2RD, 0);
      const uint4 pa = lds128(ub), pb = lds128(ub ^ 16), pc = lds128(uc), pd = lds128(uc ^ 16);
      if (prev >= 0) {
        fence_async_smem();
        __syncwarp();
        if (lane == 0) mbar_arrive(B_PREP + 8 * prev);
      }
      prev = ch;
      const uint32_t E[12] = {pa.y, pb.y, pa.z, pb.z, pa.w, pb.w, pc.x, pd.x, pc.y, pd.y, pc.z, pd.z};
      uint32_t O[11], oo[10], w7[8], w9[8];
#pragma unroll
      for (int i = 0; i < 11; i++) O[i] = __byte_perm(E[i], E[i + 1], 0x5432);
#pragma unroll
      for (int i = 0; i < 10; i++) oo[i] = hadd2(O[i], E[i + 1]);
#pragma unroll
      for (int i = 0; i < 8; i++) {
        w7[i] = hadd2(hadd2(oo[i], oo[i + 1]), hadd2(oo[i + 2], O[i + 3]));
        w9[i] = hadd2(w7[i], hadd2(E[i], E[i + 4]));
      }
      const bool wrap = q == 1 && lane == 31;
      const uint32_t oa = oa0 + ch * CB + q * 128, ob = ob0 + ch * CB + (wrap ? -128 : q * 128), m9 = wrap ? 0u : 0xffffffffu;
      sts128(oa + W7_OFF, w7[0], w7[1], w7[2], w7[3]);
      sts128(oa + W7_OFF + 2 * W_PS, w7[4], w7[5], w7[6], w7[7]);
      sts128(oa + 2 * W_PS, w9[0], w9[1], w9[2], w9[3]);
      sts128(ob, w9[4] & m9, w9[5] & m9, w9[6] & m9, w9[7] & m9);
    }
    fence_async_smem();
    __syncwarp();
    if (lane == 0) mbar_arrive(B_PREP + 8 * prev);
  }
  if (warp >= 8) {
    mbar_wait(B_TAB, 0);
    if (warp >= 12) mbar_wait(B_HST, 0);
#pragma unroll 1
    for (int ch = (warp >> 1) & 2; ch < 5; ch += (ch ? 2 : 1)) {
      conv_channel(ch, cta * 5 + ch, warp, lane, P.zero);
    }
  }
  bar_sync(6, 512);
  if (warp >= 8) {
    if (elect_one()) {
      if (warp == 15) {
        const uint8_t* hp = P.scr->h + (size_t)mt * 24 * 16384;
        const uint8_t* wp = P.scr->w2r + (size_t)ns * 24 * 10240;
        int q = 7;
        fence_async();
#pragma unroll 1
        for (int kbl = 0; kbl < 3; kbl++) {
#pragma unroll 1
          for (int r = kbl ? 0 : 4; r < 7; r++, q++) {
            const int s = q & 7, kb = 3 * (r + (r >= ns)) + kbl;
            mbar_wait(B_EMPTY2 + 8 * s, ((q >> 3) & 1) ^ 1);
            mbar_expect(B_FULL2 + 8 * s, G2_SLOT);
            bulk_g2s(SB + s * G2_SLOT, hp + kb * 16384, 16384, B_FULL2 + 8 * s);
            bulk_g2s(SB + s * G2_SLOT + 16384, wp + kb * 10240, 10240, B_FULL2 + 8 * s);
          }
        }
        mbar_expect(B_XS, 40960);
        mbar_wait(B_EMPTY2, 0);
        tma2d(SM_XT, &tmXe, ns * 80, mt * 128, B_XS);
        mbar_wait(B_SOK, 0);
        fence_async();
        mbar_wait(B_EMPTY2 + 8, 0);
        tma2d(SM_S, &tmS, mt * 128, ns * 80, B_XS);
      } else if (warp == 14) {
        bulk_s2g(P.scr->s + (cta * 5 + 3) * 1024, SM_CS, 4096);
        bulk_s2g(P.scr->s + (cta * 5 + 4) * 1024, SM_O + 4 * CB, 4096);
        bulk_commit();
        bulk_wait0();
        red_release(&P.scr->cnt[(C_S + (cta >> 4)) * 32]);
        poll_flag(&P.scr->cnt[(C_S + ns) * 32], lds32(SM_EPOCH) * 16);
        mbar_arrive(B_SOK);
      }
    }
    return;
  }

  {
    float acc[40];
    const uint64_t da0 = mkdesc(SB + (warp >> 2) * 8192, 16, 1024, 1), db0 = mkdesc(SB + 16384, 1024, 256, 3);
#pragma unroll 1
    for (int q = 0; q < 24; q++) {
      const int s = q & 7;
      mbar_wait(B_FULL2 + 8 * s, (q >> 3) & 1);
      const uint64_t da = da0 + s * (G2_SLOT >> 4), db = db0 + s * (G2_SLOT >> 4);
      wg_fence();
#pragma unroll
      for (int kk = 0; kk < 4; kk++) wgmma_n80(acc, da + kk * 2, db + (kk >> 1) * 320 + (kk & 1) * 32, kk ? 1 : q);
      wg_commit();
      wg_wait<1>();
      if ((tid & 127) == 0 && q > 0) mbar_arrive(B_EMPTY2 + 8 * ((s + 7) & 7));
    }
    mbar_wait(B_XS, 0);
    const int r0 = (warp >> 1) * 32 + (warp & 1) * 8;
    const bool sw = g >= 4;
    const uint32_t xa = SM_XT + (r0 + (lane & 7)) * 160 + (((lane >> 3) ^ ((lane >> 2) & 1)) << 4);
    const uint32_t xb = SM_XT + (r0 + (lane & 7) + (lane & 16)) * 160 + 128 + ((((lane >> 3) ^ (lane >> 2)) & 1) << 4);
    const uint32_t sa = SM_S + c * 512 + ((warp ^ c ^ (warp >> 2)) << 5) + g * 4, sd = sw ? 2048 : 0;
    uint32_t xr[2][10], w[10][2];
#pragma unroll
    for (int j = 0; j < 10; j++) {
      const uint32_t a = ((j & 1) ? sa - sd : sa + sd) + j * 2048;
      w[j][0] = lds32(a); w[j][1] = lds32(a + 256);
    }
#pragma unroll
    for (int hf = 0; hf < 2; hf++) {
      ldsm4(xa + hf * 2560, xr[hf][0], xr[hf][1], xr[hf][2], xr[hf][3]);
      ldsm4(xa + hf * 2560 + 64, xr[hf][4], xr[hf][5], xr[hf][6], xr[hf][7]);
    }
    ldsm4(xb, xr[0][8], xr[0][9], xr[1][8], xr[1][9]);
    wg_wait<0>();
    float half = 0.5f;
#pragma unroll
    for (int hf = 0; hf < 2; hf++) {
      uint32_t o[10];
#pragma unroll
      for (int j = 0; j < 10; j += 2) {
        uint32_t p[2];
#pragma unroll
        for (int h = 0; h < 2; h++) {
          const float hv = j < E2F ? 0.5f : half;
          const float h0 = hv * acc[4 * (j + h) + 2 * hf], h1 = hv * acc[4 * (j + h) + 2 * hf + 1];
          p[h] = pack_b2(fmaf(h0, tanh_fast(h0), h0), fmaf(h1, tanh_fast(h1), h1));
        }
#pragma unroll
        for (int h = 0; h < 2; h++)
          o[j + h] = bfma2(sw ? p[h ^ 1] : p[h], __byte_perm(w[j + h][0], w[j + h][1], hf ? 0x7632 : 0x5410), xr[hf][j + h]);
      }
      stsm4(xa + hf * 2560, o[0], o[1], o[2], o[3]);
      stsm4(xa + hf * 2560 + 64, o[4], o[5], o[6], o[7]);
      stsm2(xb + hf * 2560, o[8], o[9]);
      fence_async_smem();
      __syncwarp();
      if (elect_one()) {
        tma2d_store(&tmO, SM_XT + r0 * 160 + hf * 2560, ns * 80, mt * 128 + r0 + hf * 16);
        bulk_commit();
      }
      if (hf == 0) half = __uint_as_float(0x3F000000u | (lds32(SM_EPOCH) & P.zero));
    }
    bulk_wait0_read();
  }
}

typedef CUresult (*EncodeFn)(CUtensorMap*, CUtensorMapDataType, cuuint32_t, void*, const cuuint64_t*, const cuuint64_t*,
                             const cuuint32_t*, const cuuint32_t*, CUtensorMapInterleave, CUtensorMapSwizzle,
                             CUtensorMapL2promotion, CUtensorMapFloatOOBfill);

void make_map(EncodeFn enc, CUtensorMap* m, void* base, int rank, const cuuint64_t* dims, const cuuint64_t* strides,
              const cuuint32_t* box, CUtensorMapSwizzle sw) {
  const cuuint32_t es[5] = {1, 1, 1, 1, 1};
  enc(m, CU_TENSOR_MAP_DATA_TYPE_BFLOAT16, rank, base, dims, strides, box, es, CU_TENSOR_MAP_INTERLEAVE_NONE, sw,
      CU_TENSOR_MAP_L2_PROMOTION_L2_128B, CU_TENSOR_MAP_FLOAT_OOB_FILL_NONE);
}

}

extern "C" void kernel_launch(void* const* d_in, const int* in_sizes, int n_in, void* d_out, int out_size) {
  (void)in_sizes; (void)n_in; (void)out_size;
  static EncodeFn enc = nullptr;
  static int nsm = 0;
  static void *p_scr = nullptr, *p_idx = nullptr;
  if (!enc) {
    void* fn = nullptr;
    cudaDriverEntryPointQueryResult q;
    cudaGetDriverEntryPoint("cuTensorMapEncodeTiled", &fn, cudaEnableDefault, &q);
    enc = (EncodeFn)fn;
    int dev = 0;
    cudaGetDevice(&dev);
    cudaDeviceGetAttribute(&nsm, cudaDevAttrMultiProcessorCount, dev);
    cudaGetSymbolAddress(&p_scr, g_scr);
    cudaGetSymbolAddress(&p_idx, g_idx);
    cudaFuncSetAttribute(s4_ffn_kernel<true>, cudaFuncAttributeMaxDynamicSharedMemorySize, SMEM_BYTES);
    cudaFuncSetAttribute(s4_ffn_kernel<false>, cudaFuncAttributeMaxDynamicSharedMemorySize, SMEM_BYTES);
  }
  void* x = d_in[0];
  void* w1 = d_in[10];
  void* w2 = d_in[11];
  CUtensorMap tmX, tmW1, tmW2, tmU, tmXe, tmO, tmS, tmXr;
  {
    const cuuint64_t d[2] = {D_, L_}, s[1] = {D_ * 2};
    const cuuint32_t b0[2] = {32, 128}, b1[2] = {80, 128}, b2[2] = {80, 8};
    make_map(enc, &tmX, x, 2, d, s, b0, CU_TENSOR_MAP_SWIZZLE_64B);
    make_map(enc, &tmXe, x, 2, d, s, b1, CU_TENSOR_MAP_SWIZZLE_NONE);
    make_map(enc, &tmO, d_out, 2, d, s, b2, CU_TENSOR_MAP_SWIZZLE_NONE);
  }
  {
    const cuuint64_t d[3] = {64, D_, F_ / 64}, s[2] = {F_ * 2, 128};
    const cuuint32_t b[3] = {64, 32, 3};
    make_map(enc, &tmW1, w1, 3, d, s, b, CU_TENSOR_MAP_SWIZZLE_128B);
  }
  {
    const cuuint64_t d[3] = {16, F_, D_ / 16}, s[2] = {D_ * 2, 32};
    const cuuint32_t b[3] = {16, 32, 5};
    make_map(enc, &tmW2, w2, 3, d, s, b, CU_TENSOR_MAP_SWIZZLE_32B);
  }
  {
    const cuuint64_t d[3] = {16, 128, D_}, s[2] = {D_ * 32, 32};
    const cuuint32_t b[3] = {16, 136, 1};
    make_map(enc, &tmU, ((Scratch*)p_scr)->uT, 3, d, s, b, CU_TENSOR_MAP_SWIZZLE_32B);
  }
  {
    const cuuint64_t d[2] = {L_, D_}, s[1] = {L_ * 2};
    const cuuint32_t b[2] = {128, 80};
    make_map(enc, &tmS, ((Scratch*)p_scr)->s, 2, d, s, b, CU_TENSOR_MAP_SWIZZLE_NONE);
  }
  {
    const cuuint64_t d[5] = {64, 2, L_ / 8, 4, 10}, s[4] = {D_ * 2, D_ * 16, D_ * 4, 128};
    const cuuint32_t b[5] = {64, 2, 2, 4, 2};
    make_map(enc, &tmXr, x, 5, d, s, b, CU_TENSOR_MAP_SWIZZLE_128B);
  }
  Params P;
  P.are = (const __nv_bfloat16*)d_in[1]; P.aim = (const __nv_bfloat16*)d_in[2];
  P.bre = (const __nv_bfloat16*)d_in[3]; P.bim = (const __nv_bfloat16*)d_in[4];
  P.cre = (const __nv_bfloat16*)d_in[5]; P.cim = (const __nv_bfloat16*)d_in[6];
  P.logdt = (const __nv_bfloat16*)d_in[7]; P.dskip = (const __nv_bfloat16*)d_in[8];
  P.w1 = (const __nv_bfloat16*)d_in[10];
  P.w2 = (const __nv_bfloat16*)d_in[11];
  P.zero = 0;
  P.scr = (Scratch*)p_scr;
  P.idx = (const uint32_t*)p_idx;
  if (nsm == 132) s4_ffn_kernel<true><<<132, NTHREADS, SMEM_BYTES>>>(P, tmXr, tmX, tmW1, tmW2, tmU, tmXe, tmO, tmS);
  else s4_ffn_kernel<false><<<132, NTHREADS, SMEM_BYTES>>>(P, tmXr, tmX, tmW1, tmW2, tmU, tmXe, tmO, tmS);
}
```
